```python
import torch

def _softmax(x, axis=-1):
    return torch.softmax(x, dim=axis)
def _gelu(x):
    return torch.nn.functional.gelu(x, approximate="tanh")
def _silu(x):
    return torch.nn.functional.silu(x)
def _sigmoid(x):
    return torch.sigmoid(x)
def _layernorm(x, axis=-1, eps=1e-5):
    m = x.mean(dim=axis, keepdim=True)
    v = x.var(dim=axis, keepdim=True, unbiased=False)
    return (x - m) / torch.sqrt(v + eps)
def _scatter_add(tgt, idx, src, axis=0):
    return tgt.clone().index_add_(axis, idx, src)
def _segment_sum(src, seg, n):
    out = torch.zeros((n,) + src.shape[1:], dtype=src.dtype)
    return out.index_add_(0, seg, src)
def _pad(x, pw):
    flat = tuple(v for pair in reversed(pw) for v in pair)
    return torch.nn.functional.pad(x, flat)

kernel_name = 'standalone__gqa_softmax__sampling'

def setup_inputs():

    _w = (lambda a: (lambda t: t.to(torch.bfloat16) if t.is_floating_point() else t)(torch.as_tensor(a)))
    B, Hq, Hkv, Sq, Sk, D = 32, 32, 4, 4, 2048, 128
    return {
        "q": _w((lambda *s: torch.randn(*s, dtype=torch.bfloat16) * 0.8)(B, Hq, Sq, D)),
        "k": _w((lambda *s: torch.randn(*s, dtype=torch.bfloat16) * 0.8)(B, Hkv, Sk, D)),
        "v": _w((lambda *s: torch.randn(*s, dtype=torch.bfloat16) * 0.05)(B, Hkv, Sk, D)),
    }

def reference(q, k, v):
    B, Hq, Sq, D = q.shape
    Hkv = k.shape[1]
    rep = Hq // Hkv
    k = (lambda x, n, axis: torch.repeat_interleave(x, n, dim=axis))(k, rep, axis=1)
    v = (lambda x, n, axis: torch.repeat_interleave(x, n, dim=axis))(v, rep, axis=1)
    scale = D ** -0.5
    scores = torch.einsum("bhqd,bhkd->bhqk", q, k) * scale
    p = _softmax(scores, axis=-1)
    return torch.einsum("bhqk,bhkd->bhqd", p, v)
```

```cpp
#include <cuda_runtime.h>
#include <cuda_bf16.h>
#include <cuda.h>
#include <stdint.h>

namespace {

constexpr int kB = 32, kHq = 32, kHkv = 4, kSq = 4, kSk = 2048, kD = 128;
constexpr int kRowsQ = (kHq / kHkv) * kSq;
constexpr int kNumCta = kB * kHkv;
constexpr int kTileRows = 64;
constexpr int kTileBytes = kTileRows * kD * 2;
constexpr int kTileUnits = kTileRows * 2;
constexpr int kNumTiles = kSk / kTileRows;
#define PACE 1
#define BIAS 704
#define WMIN 3
#define WMAX 7
#define NSTAGE 10
#define WINDOW 4
#define LAG 2
constexpr int kStages = NSTAGE;
constexpr int kWindow = WINDOW;
constexpr int kLag = LAG;
constexpr int kChunks = 2 * kNumTiles;
constexpr int kNumWG = 2;
constexpr int kThreads = kNumWG * 128 + 64;
constexpr int kXchgBytes = kNumWG * 128 * 16 * 4;
constexpr int kSmemBytes = kStages * kTileBytes + kXchgBytes + 1024;

__device__ __forceinline__ uint32_t smem_u32(const void* p) { return (uint32_t)__cvta_generic_to_shared(p); }
__device__ __forceinline__ void mbar_init(uint32_t bar, uint32_t cnt) {
    asm volatile("mbarrier.init.shared::cta.b64 [%0], %1;" ::"r"(bar), "r"(cnt) : "memory");
}
__device__ __forceinline__ void mbar_expect_tx(uint32_t bar, uint32_t bytes) {
    asm volatile("mbarrier.arrive.expect_tx.shared::cta.b64 _, [%0], %1;" ::"r"(bar), "r"(bytes) : "memory");
}
__device__ __forceinline__ void mbar_arrive(uint32_t bar) {
    asm volatile("mbarrier.arrive.shared::cta.b64 _, [%0];" ::"r"(bar) : "memory");
}
__device__ __forceinline__ void mbar_wait(uint32_t bar, uint32_t parity) {
    asm volatile(
        "{\n"
        ".reg .pred p;\n"
        "WAIT_LOOP:\n"
        "mbarrier.try_wait.parity.shared::cta.b64 p, [%0], %1;\n"
        "@p bra WAIT_DONE;\n"
        "bra WAIT_LOOP;\n"
        "WAIT_DONE:\n"
        "}\n" ::"r"(bar), "r"(parity) : "memory");
}
__device__ __forceinline__ bool mbar_test(uint32_t bar, uint32_t parity) {
    uint32_t ok;
    asm volatile("{\n.reg .pred p;\nmbarrier.test_wait.parity.shared::cta.b64 p, [%1], %2;\nselp.u32 %0, 1, 0, p;\n}\n"
                 : "=r"(ok) : "r"(bar), "r"(parity) : "memory");
    return ok != 0;
}
__device__ __forceinline__ void tma_load(uint32_t dst, const CUtensorMap* tm, uint32_t bar, int unit) {
    asm volatile(
        "cp.async.bulk.tensor.2d.shared::cluster.global.mbarrier::complete_tx::bytes [%0], [%1, {%3, %4}], [%2];"
        ::"r"(dst), "l"(tm), "r"(bar), "r"(0), "r"(unit) : "memory");
}
__device__ __forceinline__ void wg_fence() { asm volatile("wgmma.fence.sync.aligned;" ::: "memory"); }
__device__ __forceinline__ void wg_commit() { asm volatile("wgmma.commit_group.sync.aligned;" ::: "memory"); }
template <int N> __device__ __forceinline__ void wg_wait() { asm volatile("wgmma.wait_group.sync.aligned %0;" ::"n"(N) : "memory"); }
__device__ __forceinline__ void consumer_sync() { asm volatile("bar.sync 1, %0;" ::"n"(kNumWG * 128) : "memory"); }

__device__ __forceinline__ uint64_t make_desc(uint32_t addr) {
    return (uint64_t)((addr & 0x3FFFF) >> 4) | ((uint64_t)1 << 16) | ((uint64_t)(1024 >> 4) << 32) | ((uint64_t)1 << 62);
}

template <int TB>
__device__ __forceinline__ void wgmma_64x64(float (&d)[32], const uint32_t (&a)[4], uint64_t desc, int scale_d) {
    asm volatile(
        "{\n.reg .pred p;\nsetp.ne.b32 p, %37, 0;\n"
        "wgmma.mma_async.sync.aligned.m64n64k16.f32.bf16.bf16 "
        "{%0,%1,%2,%3,%4,%5,%6,%7,%8,%9,%10,%11,%12,%13,%14,%15,"
        "%16,%17,%18,%19,%20,%21,%22,%23,%24,%25,%26,%27,%28,%29,%30,%31},"
        "{%32,%33,%34,%35}, %36, p, 1, 1, %38;\n}\n"
        : "+f"(d[0]), "+f"(d[1]), "+f"(d[2]), "+f"(d[3]), "+f"(d[4]), "+f"(d[5]), "+f"(d[6]), "+f"(d[7]),
          "+f"(d[8]), "+f"(d[9]), "+f"(d[10]), "+f"(d[11]), "+f"(d[12]), "+f"(d[13]), "+f"(d[14]), "+f"(d[15]),
          "+f"(d[16]), "+f"(d[17]), "+f"(d[18]), "+f"(d[19]), "+f"(d[20]), "+f"(d[21]), "+f"(d[22]), "+f"(d[23]),
          "+f"(d[24]), "+f"(d[25]), "+f"(d[26]), "+f"(d[27]), "+f"(d[28]), "+f"(d[29]), "+f"(d[30]), "+f"(d[31])
        : "r"(a[0]), "r"(a[1]), "r"(a[2]), "r"(a[3]), "l"(desc), "r"(scale_d), "n"(TB));
}

__device__ __forceinline__ uint32_t ldg_nc(const uint32_t* p) {
    uint32_t v; asm volatile("ld.global.u32 %0, [%1];" : "=r"(v) : "l"(p) : "memory"); return v;
}
__device__ __forceinline__ float ex2(float x) { float y; asm("ex2.approx.ftz.f32 %0, %1;" : "=f"(y) : "f"(x)); return y; }
__device__ __forceinline__ uint32_t pack_bf16(float lo, float hi) {
    uint32_t r; asm("cvt.rn.bf16x2.f32 %0, %1, %2;" : "=r"(r) : "f"(hi), "f"(lo)); return r;
}

#define CREC(i) do {} while (0)
#define TREC(i) do {} while (0)
#define TREC0(cond, i) do {} while (0)

__device__ unsigned int g_landed;

__device__ __forceinline__ void chunk_of(int j, bool& is_v, int& tile) {
    const int jj = j - kLag;
    if (jj < 0) { is_v = false; tile = j; }
    else if (jj < 2 * (kNumTiles - kLag)) { is_v = jj & 1; tile = (jj >> 1) + (is_v ? 0 : kLag); }
    else { is_v = true; tile = jj - (kNumTiles - kLag); }
}

__global__ void __launch_bounds__(kThreads, 1)
gqa_decode_kernel(const __grid_constant__ CUtensorMap tmK, const __grid_constant__ CUtensorMap tmV,
                  const __nv_bfloat16* __restrict__ q, __nv_bfloat16* __restrict__ out) {
    extern __shared__ uint8_t smem_raw[];
    __shared__ __align__(8) uint64_t bars[2 * kStages];
    __shared__ float s_m[kNumWG][kRowsQ], s_l[kNumWG][kRowsQ];
    __shared__ volatile int s_pace[2];
    const uint32_t tiles = (smem_u32(smem_raw) + 1023u) & ~1023u;
    const uint32_t full0 = smem_u32(&bars[0]);
    const uint32_t empty0 = full0 + 8 * kStages;
    const int bh = blockIdx.x;
    const int unit0 = bh * (kSk * 2);
    if (threadIdx.x == 0) {
        TREC(0);
#pragma unroll
        for (int j = 0; j < kWindow; j++) mbar_init(full0 + 8 * j, 1);
        asm volatile("fence.mbarrier_init.release.cluster;" ::: "memory");
#pragma unroll
        for (int j = 0; j < kWindow; j++) {
            bool is_v; int tile;
            chunk_of(j, is_v, tile);
            mbar_expect_tx(full0 + 8 * j, kTileBytes);
            tma_load(tiles + j * kTileBytes, is_v ? &tmV : &tmK, full0 + 8 * j, unit0 + tile * kTileUnits);
            if (j == 0) TREC(1);
        }
        TREC(2);
#pragma unroll
        for (int s = kWindow; s < kStages; s++) mbar_init(full0 + 8 * s, 1);
#pragma unroll
        for (int s = 0; s < kStages; s++) mbar_init(empty0 + 8 * s, kNumWG * 4);
        asm volatile("fence.mbarrier_init.release.cluster;" ::: "memory");
        s_pace[0] = 0; s_pace[1] = 0;
    }
    const int warp = __shfl_sync(0xffffffffu, threadIdx.x >> 5, 0), lane = threadIdx.x & 31;

    if (warp == kNumWG * 4) {
        __syncthreads();
        bool inflight = lane < kWindow;
        uint32_t fph = 0;
        int issued = kWindow, arrived = 0, slot = kWindow % kStages, eph = (kWindow / kStages) & 1;
        while (issued < kChunks) {
            const bool rdy = inflight && mbar_test(full0 + 8 * lane, fph);
            const int nrdy = __popc(__ballot_sync(0xffffffffu, rdy));
            arrived += nrdy;
            if (nrdy && lane == 0) asm volatile("red.relaxed.gpu.global.add.u32 [%0], %1;" ::"l"(&g_landed), "r"(nrdy) : "memory");
            const int credit = s_pace[0] + BIAS - bh;
            if (rdy) { inflight = false; fph ^= 1; }
            while (issued < kChunks && (issued - arrived < WMIN || (issued - arrived < WMAX && issued * kNumCta <= credit))) {
                if (!mbar_test(empty0 + 8 * slot, eph ^ 1)) break;
                if (lane == slot) {
                    bool is_v; int tile;
                    chunk_of(issued, is_v, tile);
                    mbar_expect_tx(full0 + 8 * slot, kTileBytes);
                    tma_load(tiles + slot * kTileBytes, is_v ? &tmV : &tmK, full0 + 8 * slot, unit0 + tile * kTileUnits);
                    inflight = true;
                }
                issued++;
                if (++slot == kStages) { slot = 0; eph ^= 1; }
            }
        }
        if (lane == 0) {
            s_pace[1] = 1;
            if (arrived < kChunks) asm volatile("red.relaxed.gpu.global.add.u32 [%0], %1;" ::"l"(&g_landed), "r"(kChunks - arrived) : "memory");
        }
    } else if (warp == kNumWG * 4 + 1) {
        __syncthreads();
        if (lane == 0) {
            int best = 0;
            while (!s_pace[1]) {
                unsigned v;
                asm volatile("ld.relaxed.gpu.global.u32 %0, [%1];" : "=r"(v) : "l"(&g_landed) : "memory");
                best = max(best, (int)(v & (kNumCta * kChunks - 1)));
                s_pace[0] = best;
            }
        }
    } else {
        const int wg = warp >> 2;
        const int g = lane >> 2, t = lane & 3;
        const int row = (warp & 3) * 8 + g;
        uint32_t qa[4][4];
        {
            const uint32_t* qp = reinterpret_cast<const uint32_t*>(q + (size_t)(bh * kRowsQ + row) * kD) + t;
#pragma unroll
            for (int kk = 0; kk < 4; kk++) {
                qa[kk][0] = ldg_nc(qp + kk * 8);
                qa[kk][1] = ldg_nc(qp + 32 + kk * 8);
                qa[kk][2] = ldg_nc(qp + kk * 8 + 4);
                qa[kk][3] = ldg_nc(qp + 32 + kk * 8 + 4);
            }
        }
        uint4* op = reinterpret_cast<uint4*>(out + (size_t)(bh * kRowsQ + (warp & 3) * 8 + (lane >> 3)) * kD + wg * 64) + (lane & 7);
        asm volatile("add.u64 %0, %0, 0;" : "+l"(op));
        const uint32_t sel_lo0 = wg ? 0x1044u : 0x4410u, sel_lo1 = wg ? 0x4410u : 0x1044u;
        const uint32_t sel_hi0 = wg ? 0x3244u : 0x4432u, sel_hi1 = wg ? 0x4432u : 0x3244u;
        float o[32];
#pragma unroll
        for (int i = 0; i < 32; i++) o[i] = 0.f;
        float m = -INFINITY;
        float mo = -INFINITY;
        float l = 0.f;
        float sq[kLag + 1][8];
        const float c = 0.08838834764831845f * 1.4426950408889634f;
        const uint32_t mytiles = tiles + wg * (kTileBytes / kNumWG);
        __syncthreads();

        int s = 0, ph = 0;
        int vslot = -1;

        auto qk_step = [&](float (&dst)[8]) {
            float sc[32];
            mbar_wait(full0 + 8 * s, ph);
            const uint64_t dk = make_desc(mytiles + s * kTileBytes);
            wg_fence();
#pragma unroll
            for (int kk = 0; kk < 4; kk++) wgmma_64x64<0>(sc, qa[kk], dk + kk * 2, kk);
            wg_commit();
            wg_wait<0>();
#pragma unroll
            for (int i = 0; i < 32; i++) asm volatile("" : "+f"(sc[i]) :: "memory");
            if (lane == 0) {
                mbar_arrive(empty0 + 8 * s);
                if (vslot >= 0) mbar_arrive(empty0 + 8 * vslot);
            }
            if (++s == kStages) { s = 0; ph ^= 1; }
#pragma unroll
            for (int i = 0; i < 8; i++) dst[i] = sc[4 * i] + sc[4 * i + 3];
            float mx = fmaxf(fmaxf(fmaxf(dst[0], dst[1]), fmaxf(dst[2], dst[3])), fmaxf(fmaxf(dst[4], dst[5]), fmaxf(dst[6], dst[7])));
            mx = fmaxf(mx, __shfl_xor_sync(0xffffffffu, mx, 1));
            mx = fmaxf(mx, __shfl_xor_sync(0xffffffffu, mx, 2));
            m = fmaxf(m, mx);
        };
        auto make_p = [&](const float (&src)[8], float mc, uint32_t (&pa)[4][4]) {
            float ps = 0.f;
#pragma unroll
            for (int j = 0; j < 4; j++) {
                const float p0 = ex2(fmaf(src[2 * j], c, -mc));
                const float p1 = ex2(fmaf(src[2 * j + 1], c, -mc));
                ps += p0 + p1;
                const uint32_t pk = pack_bf16(p0, p1);
                pa[j][0] = __byte_perm(pk, 0, sel_lo0);
                pa[j][1] = __byte_perm(pk, 0, sel_lo1);
                pa[j][2] = __byte_perm(pk, 0, sel_hi0);
                pa[j][3] = __byte_perm(pk, 0, sel_hi1);
#pragma unroll
                for (int r = 0; r < 4; r++) asm volatile("" : "+r"(pa[j][r]));
            }
            return ps;
        };
        auto rescale = [&]() {
            const float alpha = ex2((mo - m) * c);
            mo = m;
            l *= alpha;
#pragma unroll
            for (int i = 0; i < 32; i++) { o[i] *= alpha; asm volatile("" : "+f"(o[i])); }
        };
        auto pv_step = [&](const uint32_t (&pa)[4][4]) {
            mbar_wait(full0 + 8 * s, ph);
            const uint64_t dv = make_desc(mytiles + s * kTileBytes);
            wg_fence();
#pragma unroll
            for (int j = 0; j < 4; j++) wgmma_64x64<1>(o, pa[j], dv + j * (2048 >> 4), 1);
            wg_commit();
            vslot = s;
            if (++s == kStages) { s = 0; ph ^= 1; }
        };

#pragma unroll
        for (int i = 0; i < kLag; i++) qk_step(sq[i]);
        TREC0(true, 3);
#pragma unroll 1
        for (int tile = 0; tile < kNumTiles - kLag - 1; tile++) {
            qk_step(sq[kLag]);
            uint32_t pa[4][4];
            rescale();
            l += make_p(sq[0], m * c, pa);
            pv_step(pa);
#pragma unroll
            for (int i = 0; i < kLag; i++)
#pragma unroll
                for (int e = 0; e < 8; e++) sq[i][e] = sq[i + 1][e];
        }
        qk_step(sq[kLag]);
        TREC0(true, 4);
        if (t == 0) s_m[wg][row] = m;
        consumer_sync();
        m = fmaxf(m, s_m[wg ^ 1][row]);
        rescale();
        uint32_t pa[kLag + 1][4][4];
        TREC0(true, 8);
#pragma unroll
        for (int i = 0; i <= kLag; i++) {
            l += make_p(sq[i], m * c, pa[i]);
            if (i == kLag) {
                l += __shfl_xor_sync(0xffffffffu, l, 1);
                l += __shfl_xor_sync(0xffffffffu, l, 2);
                if (t == 0) s_l[wg][row] = l;
                asm volatile("bar.arrive %0, %1;" ::"r"(2 + wg), "n"(kNumWG * 128) : "memory");
            }
            pv_step(pa[i]);
        }
        TREC0(true, 5);
        asm volatile("bar.sync %0, %1;" ::"r"(3 - wg), "n"(kNumWG * 128) : "memory");
        float inv;
        asm volatile("rcp.approx.ftz.f32 %0, %1;" : "=f"(inv) : "f"(l + s_l[wg ^ 1][row]));
        const uint32_t xchg = tiles + kStages * kTileBytes + (threadIdx.x & 127) * 8;
        const uint32_t stage = tiles + warp * 1024;
        const uint32_t st_addr = stage + (lane & 7) * 128, ld_addr = stage + (lane >> 3) * 128;
        wg_wait<0>();
#pragma unroll
        for (int i = 0; i < 32; i++) asm volatile("" : "+f"(o[i]) :: "memory");
        TREC0(true, 6);
        CREC(0);

#pragma unroll
        for (int i = 0; i < 8; i++)
            asm volatile("st.shared.v2.f32 [%0], {%1,%2};" ::"r"(xchg + (wg * 8 + i) * 1024), "f"(o[4 * i + 2]), "f"(o[4 * i + 3]) : "memory");
        consumer_sync();
        CREC(1);
        CREC(2);
        uint32_t r[8];
#pragma unroll
        for (int i = 0; i < 8; i++) {
            float x, y;
            asm volatile("ld.shared.v2.f32 {%0,%1}, [%2];" : "=f"(x), "=f"(y) : "r"(xchg + ((wg ^ 1) * 8 + i) * 1024) : "memory");
            r[i] = pack_bf16((o[4 * i] + x) * inv, (o[4 * i + 1] + y) * inv);
        }
        CREC(3);
#pragma unroll
        for (int h = 0; h < 2; h++)
            asm volatile("stmatrix.sync.aligned.m8n8.x4.shared.b16 [%0], {%1,%2,%3,%4};"
                         ::"r"(st_addr + (((4 * h + (lane >> 3)) ^ (lane & 7)) << 4)),
                           "r"(r[4 * h]), "r"(r[4 * h + 1]), "r"(r[4 * h + 2]), "r"(r[4 * h + 3]) : "memory");
        __syncwarp();
#pragma unroll
        for (int h = 0; h < 2; h++) {
            uint32_t a0, a1, a2, a3;
            asm volatile("ld.shared.v4.b32 {%0,%1,%2,%3}, [%4];" : "=r"(a0), "=r"(a1), "=r"(a2), "=r"(a3)
                         : "r"(ld_addr + h * 512 + (((lane & 7) ^ (4 * h + (lane >> 3))) << 4)) : "memory");
            asm volatile("st.global.v4.u32 [%0], {%1,%2,%3,%4};" ::"l"(op + h * 4 * (kD / 8)), "r"(a0), "r"(a1), "r"(a2), "r"(a3) : "memory");
        }
        CREC(4);
        TREC0(true, 7);
    }
}

typedef CUresult (*EncodeTiledFn)(CUtensorMap*, CUtensorMapDataType, cuuint32_t, void*, const cuuint64_t*,
                                  const cuuint64_t*, const cuuint32_t*, const cuuint32_t*, CUtensorMapInterleave,
                                  CUtensorMapSwizzle, CUtensorMapL2promotion, CUtensorMapFloatOOBfill);

void make_map(EncodeTiledFn enc, CUtensorMap* tm, const void* base) {
    const cuuint64_t dims[2] = {64, (cuuint64_t)kB * kHkv * kSk * 2};
    const cuuint64_t strides[1] = {128};
    const cuuint32_t box[2] = {64, (cuuint32_t)kTileUnits};
    const cuuint32_t estr[2] = {1, 1};
    enc(tm, CU_TENSOR_MAP_DATA_TYPE_BFLOAT16, 2, const_cast<void*>(base), dims, strides, box, estr,
        CU_TENSOR_MAP_INTERLEAVE_NONE, CU_TENSOR_MAP_SWIZZLE_128B, CU_TENSOR_MAP_L2_PROMOTION_NONE,
        CU_TENSOR_MAP_FLOAT_OOB_FILL_NONE);
}

}

extern "C" void kernel_launch(void* const* d_in, const int* in_sizes, int n_in, void* d_out, int out_size) {
    (void)in_sizes; (void)n_in; (void)out_size;
    static EncodeTiledFn enc = nullptr;
    if (!enc) {
        cudaDriverEntryPointQueryResult qr;
        cudaGetDriverEntryPoint("cuTensorMapEncodeTiled", (void**)&enc, cudaEnableDefault, &qr);
        cudaFuncSetAttribute(gqa_decode_kernel, cudaFuncAttributeMaxDynamicSharedMemorySize, kSmemBytes);
    }
    CUtensorMap tmK, tmV;
    make_map(enc, &tmK, d_in[1]);
    make_map(enc, &tmV, d_in[2]);
    gqa_decode_kernel<<<kNumCta, kThreads, kSmemBytes>>>(tmK, tmV, (const __nv_bfloat16*)d_in[0], (__nv_bfloat16*)d_out);
}
```

```cpp
#include <cuda_runtime.h>
#include <cuda_bf16.h>
#include <cuda.h>
#include <stdint.h>

namespace {

constexpr int kB = 32, kHq = 32, kHkv = 4, kSq = 4, kSk = 2048, kD = 128;
constexpr int kRowsQ = (kHq / kHkv) * kSq;
constexpr int kNumCta = kB * kHkv;
constexpr int kTileRows = 64;
constexpr int kTileBytes = kTileRows * kD * 2;
constexpr int kTileUnits = kTileRows * 2;
constexpr int kNumTiles = kSk / kTileRows;
constexpr int kChunks = 2 * kNumTiles;
constexpr int kRun = 4;
#define NSTAGE 10
#define BIAS 704
#define WMIN 3
#define WMAX 7
constexpr int kStages = NSTAGE;
constexpr int kWindow = 4;
constexpr int kCredit = BIAS;
constexpr int kMinFlight = WMIN, kMaxFlight = WMAX;
constexpr int kThreads = 128 + 64;
constexpr int kSmemBytes = kStages * kTileBytes + kRowsQ * kD * 2 + 1024;

__device__ __forceinline__ uint32_t smem_u32(const void* p) { return (uint32_t)__cvta_generic_to_shared(p); }
__device__ __forceinline__ void mbar_init(uint32_t bar, uint32_t cnt) {
    asm volatile("mbarrier.init.shared::cta.b64 [%0], %1;" ::"r"(bar), "r"(cnt) : "memory");
}
__device__ __forceinline__ void mbar_expect_tx(uint32_t bar, uint32_t bytes) {
    asm volatile("mbarrier.arrive.expect_tx.shared::cta.b64 _, [%0], %1;" ::"r"(bar), "r"(bytes) : "memory");
}
__device__ __forceinline__ void mbar_arrive(uint32_t bar) {
    asm volatile("mbarrier.arrive.shared::cta.b64 _, [%0];" ::"r"(bar) : "memory");
}
__device__ __forceinline__ void mbar_wait(uint32_t bar, uint32_t parity) {
    asm volatile(
        "{\n"
        ".reg .pred p;\n"
        "WAIT_LOOP:\n"
        "mbarrier.try_wait.parity.shared::cta.b64 p, [%0], %1;\n"
        "@p bra WAIT_DONE;\n"
        "bra WAIT_LOOP;\n"
        "WAIT_DONE:\n"
        "}\n" ::"r"(bar), "r"(parity) : "memory");
}
__device__ __forceinline__ bool mbar_test(uint32_t bar, uint32_t parity) {
    uint32_t ok;
    asm volatile("{\n.reg .pred p;\nmbarrier.test_wait.parity.shared::cta.b64 p, [%1], %2;\nselp.u32 %0, 1, 0, p;\n}\n"
                 : "=r"(ok) : "r"(bar), "r"(parity) : "memory");
    return ok != 0;
}
__device__ __forceinline__ void tma_load(uint32_t dst, const CUtensorMap* tm, uint32_t bar, int unit) {
    asm volatile(
        "cp.async.bulk.tensor.2d.shared::cluster.global.mbarrier::complete_tx::bytes [%0], [%1, {%3, %4}], [%2];"
        ::"r"(dst), "l"(tm), "r"(bar), "r"(0), "r"(unit) : "memory");
}
__device__ __forceinline__ void wg_fence() { asm volatile("wgmma.fence.sync.aligned;" ::: "memory"); }
__device__ __forceinline__ void wg_commit() { asm volatile("wgmma.commit_group.sync.aligned;" ::: "memory"); }
__device__ __forceinline__ void wg_wait() { asm volatile("wgmma.wait_group.sync.aligned 0;" ::: "memory"); }

__device__ __forceinline__ uint64_t make_desc(uint32_t addr) {
    return (uint64_t)((addr & 0x3FFFF) >> 4) | ((uint64_t)1 << 16) | ((uint64_t)(1024 >> 4) << 32) | ((uint64_t)1 << 62);
}

__device__ __forceinline__ void wgmma_qk(float (&d)[64], const uint32_t (&a)[4], uint64_t desc, int scale_d) {
    asm volatile(
        "{\n.reg .pred p;\nsetp.ne.b32 p, %69, 0;\n"
        "wgmma.mma_async.sync.aligned.m64n128k16.f32.bf16.bf16 "
        "{%0,%1,%2,%3,%4,%5,%6,%7,%8,%9,%10,%11,%12,%13,%14,%15,"
        "%16,%17,%18,%19,%20,%21,%22,%23,%24,%25,%26,%27,%28,%29,%30,%31,"
        "%32,%33,%34,%35,%36,%37,%38,%39,%40,%41,%42,%43,%44,%45,%46,%47,"
        "%48,%49,%50,%51,%52,%53,%54,%55,%56,%57,%58,%59,%60,%61,%62,%63},"
        "{%64,%65,%66,%67}, %68, p, 1, 1, 0;\n}\n"
        : "+f"(d[0]), "+f"(d[1]), "+f"(d[2]), "+f"(d[3]), "+f"(d[4]), "+f"(d[5]), "+f"(d[6]), "+f"(d[7]),
          "+f"(d[8]), "+f"(d[9]), "+f"(d[10]), "+f"(d[11]), "+f"(d[12]), "+f"(d[13]), "+f"(d[14]), "+f"(d[15]),
          "+f"(d[16]), "+f"(d[17]), "+f"(d[18]), "+f"(d[19]), "+f"(d[20]), "+f"(d[21]), "+f"(d[22]), "+f"(d[23]),
          "+f"(d[24]), "+f"(d[25]), "+f"(d[26]), "+f"(d[27]), "+f"(d[28]), "+f"(d[29]), "+f"(d[30]), "+f"(d[31]),
          "+f"(d[32]), "+f"(d[33]), "+f"(d[34]), "+f"(d[35]), "+f"(d[36]), "+f"(d[37]), "+f"(d[38]), "+f"(d[39]),
          "+f"(d[40]), "+f"(d[41]), "+f"(d[42]), "+f"(d[43]), "+f"(d[44]), "+f"(d[45]), "+f"(d[46]), "+f"(d[47]),
          "+f"(d[48]), "+f"(d[49]), "+f"(d[50]), "+f"(d[51]), "+f"(d[52]), "+f"(d[53]), "+f"(d[54]), "+f"(d[55]),
          "+f"(d[56]), "+f"(d[57]), "+f"(d[58]), "+f"(d[59]), "+f"(d[60]), "+f"(d[61]), "+f"(d[62]), "+f"(d[63])
        : "r"(a[0]), "r"(a[1]), "r"(a[2]), "r"(a[3]), "l"(desc), "r"(scale_d));
}

__device__ __forceinline__ void wgmma_pv(float (&d)[32], const uint32_t (&a)[4], uint64_t desc) {
    asm volatile(
        "wgmma.mma_async.sync.aligned.m64n64k16.f32.bf16.bf16 "
        "{%0,%1,%2,%3,%4,%5,%6,%7,%8,%9,%10,%11,%12,%13,%14,%15,"
        "%16,%17,%18,%19,%20,%21,%22,%23,%24,%25,%26,%27,%28,%29,%30,%31},"
        "{%32,%33,%34,%35}, %36, 1, 1, 1, 1;\n"
        : "+f"(d[0]), "+f"(d[1]), "+f"(d[2]), "+f"(d[3]), "+f"(d[4]), "+f"(d[5]), "+f"(d[6]), "+f"(d[7]),
          "+f"(d[8]), "+f"(d[9]), "+f"(d[10]), "+f"(d[11]), "+f"(d[12]), "+f"(d[13]), "+f"(d[14]), "+f"(d[15]),
          "+f"(d[16]), "+f"(d[17]), "+f"(d[18]), "+f"(d[19]), "+f"(d[20]), "+f"(d[21]), "+f"(d[22]), "+f"(d[23]),
          "+f"(d[24]), "+f"(d[25]), "+f"(d[26]), "+f"(d[27]), "+f"(d[28]), "+f"(d[29]), "+f"(d[30]), "+f"(d[31])
        : "r"(a[0]), "r"(a[1]), "r"(a[2]), "r"(a[3]), "l"(desc));
}

__device__ __forceinline__ uint32_t ldg_u32(const uint32_t* p) {
    uint32_t v; asm volatile("ld.global.u32 %0, [%1];" : "=r"(v) : "l"(p) : "memory"); return v;
}
__device__ __forceinline__ float ex2(float x) { float y; asm("ex2.approx.ftz.f32 %0, %1;" : "=f"(y) : "f"(x)); return y; }
__device__ __forceinline__ uint32_t pack_bf16(float lo, float hi) {
    uint32_t r; asm("cvt.rn.bf16x2.f32 %0, %1, %2;" : "=r"(r) : "f"(hi), "f"(lo)); return r;
}

__device__ unsigned int g_landed;

__device__ __forceinline__ void chunk_of(int j, bool& is_v, int& tile) {
    is_v = (j / kRun) & 1;
    tile = (j / (2 * kRun)) * kRun + j % kRun;
}

__global__ void __launch_bounds__(kThreads, 1)
gqa_decode_kernel(const __grid_constant__ CUtensorMap tmK, const __grid_constant__ CUtensorMap tmV,
                  const __nv_bfloat16* __restrict__ q, __nv_bfloat16* __restrict__ out) {
    extern __shared__ uint8_t smem_raw[];
    __shared__ __align__(8) uint64_t bars[2 * kStages];
    __shared__ volatile int s_pace[3];
    const int bh = blockIdx.x;
    const int unit0 = bh * (kSk * 2);
    const int lane = threadIdx.x & 31;

    if (threadIdx.x == 128) {
        const uint32_t tiles = (smem_u32(smem_raw) + 1023u) & ~1023u;
        const uint32_t full0 = smem_u32(&bars[0]), empty0 = full0 + 8 * kStages;
#pragma unroll
        for (int j = 0; j < kWindow; j++) mbar_init(full0 + 8 * j, 1);
        asm volatile("fence.mbarrier_init.release.cluster;" ::: "memory");
#pragma unroll
        for (int j = 0; j < kWindow; j++) {
            bool is_v; int tile;
            chunk_of(j, is_v, tile);
            mbar_expect_tx(full0 + 8 * j, kTileBytes);
            tma_load(tiles + j * kTileBytes, is_v ? &tmV : &tmK, full0 + 8 * j, unit0 + tile * kTileUnits);
        }
#pragma unroll
        for (int s = kWindow; s < kStages; s++) mbar_init(full0 + 8 * s, 1);
#pragma unroll
        for (int s = 0; s < kStages; s++) mbar_init(empty0 + 8 * s, 4);
        asm volatile("fence.mbarrier_init.release.cluster;" ::: "memory");
        s_pace[0] = 0; s_pace[1] = 0;
    }

    if (threadIdx.x >= 160) {
        asm volatile("bar.sync 2, 64;" ::: "memory");
        if (lane == 0) {
            int best = 0;
            while (!s_pace[1]) {
                unsigned v;
                asm volatile("ld.relaxed.gpu.global.u32 %0, [%1];" : "=r"(v) : "l"(&g_landed) : "memory");
                best = max(best, (int)(v & (kNumCta * kChunks - 1)));
                s_pace[0] = best;
            }
        }
    } else if (threadIdx.x >= 128) {
        const uint32_t tiles = (smem_u32(smem_raw) + 1023u) & ~1023u;
        const uint32_t full0 = smem_u32(&bars[0]), empty0 = full0 + 8 * kStages;
        __syncwarp();
        asm volatile("bar.arrive 1, 160;" ::: "memory");
        asm volatile("bar.arrive 2, 64;" ::: "memory");
        bool inflight = lane < kWindow;
        uint32_t fph = 0;
        int issued = kWindow, arrived = 0, slot = kWindow % kStages, eph = (kWindow / kStages) & 1;
        while (issued < kChunks) {
            const bool rdy = inflight && mbar_test(full0 + 8 * lane, fph);
            const int nrdy = __popc(__ballot_sync(0xffffffffu, rdy));
            arrived += nrdy;
            if (nrdy && lane == 0) asm volatile("red.relaxed.gpu.global.add.u32 [%0], %1;" ::"l"(&g_landed), "r"(nrdy) : "memory");
            const int credit = s_pace[0] + kCredit - bh;
            if (rdy) { inflight = false; fph ^= 1; }
            while (issued < kChunks &&
                   (issued - arrived < kMinFlight || (issued - arrived < kMaxFlight && issued * kNumCta <= credit))) {
                if (!mbar_test(empty0 + 8 * slot, eph ^ 1)) break;
                if (lane == slot) {
                    bool is_v; int tile;
                    chunk_of(issued, is_v, tile);
                    mbar_expect_tx(full0 + 8 * slot, kTileBytes);
                    tma_load(tiles + slot * kTileBytes, is_v ? &tmV : &tmK, full0 + 8 * slot, unit0 + tile * kTileUnits);
                    inflight = true;
                }
                issued++;
                if (++slot == kStages) { slot = 0; eph ^= 1; }
            }
        }
        if (lane == 0) {
            s_pace[1] = 1;
            asm volatile("red.relaxed.gpu.global.add.u32 [%0], %1;" ::"l"(&g_landed), "r"(kChunks - arrived) : "memory");
        }
    } else {
        const int warp = __shfl_sync(0xffffffffu, threadIdx.x >> 5, 0);
        const uint32_t tiles = __shfl_sync(0xffffffffu, (smem_u32(smem_raw) + 1023u) & ~1023u, 0);
        const uint32_t full0 = __shfl_sync(0xffffffffu, smem_u32(&bars[0]), 0), empty0 = full0 + 8 * kStages;
        const int g = lane >> 2, t = lane & 3;
        uint32_t qa[4][4];
        {
            const uint32_t* qp = reinterpret_cast<const uint32_t*>(q + (size_t)(bh * kRowsQ + warp * 8 + g) * kD) + t;
#pragma unroll
            for (int kk = 0; kk < 4; kk++) {
                qa[kk][0] = ldg_u32(qp + kk * 8);
                qa[kk][1] = ldg_u32(qp + 32 + kk * 8);
                qa[kk][2] = ldg_u32(qp + kk * 8 + 4);
                qa[kk][3] = ldg_u32(qp + 32 + kk * 8 + 4);
            }
        }
        uint4* op = reinterpret_cast<uint4*>(out + (size_t)(bh * kRowsQ + warp * 8 + (lane >> 4)) * kD) + (lane & 15);
        asm volatile("add.u64 %0, %0, 0;" : "+l"(op));
        float o[32];
#pragma unroll
        for (int i = 0; i < 32; i++) o[i] = 0.f;
        float m = -INFINITY;
        float mo = -INFINITY;
        float l = 0.f;
        float sq[kRun][16];
        const float c = 0.08838834764831845f * 1.4426950408889634f;
        asm volatile("bar.sync 1, 160;" ::: "memory");

        int s = 0, ph = 0;

        auto qk_step = [&](float (&dst)[16]) {
            float sc[64];
            mbar_wait(full0 + 8 * s, ph);
            const uint64_t dk = make_desc(tiles + s * kTileBytes);
            wg_fence();
#pragma unroll
            for (int kk = 0; kk < 4; kk++) wgmma_qk(sc, qa[kk], dk + kk * 2, kk);
            wg_commit();
            wg_wait();
            if (lane == 0) mbar_arrive(empty0 + 8 * s);
            if (++s == kStages) { s = 0; ph ^= 1; }
#pragma unroll
            for (int i = 0; i < 64; i++) asm volatile("" : "+f"(sc[i]) :: "memory");
#pragma unroll
            for (int i = 0; i < 16; i++) dst[i] = sc[4 * i] + sc[4 * i + 3];
            float mx[4];
#pragma unroll
            for (int i = 0; i < 4; i++) mx[i] = fmaxf(fmaxf(dst[4 * i], dst[4 * i + 1]), fmaxf(dst[4 * i + 2], dst[4 * i + 3]));
            float mm = fmaxf(fmaxf(mx[0], mx[1]), fmaxf(mx[2], mx[3]));
            mm = fmaxf(mm, __shfl_xor_sync(0xffffffffu, mm, 1));
            mm = fmaxf(mm, __shfl_xor_sync(0xffffffffu, mm, 2));
            m = fmaxf(m, mm);
        };
        auto expo = [&](float (&x)[16]) {
            const float mc = m * c;
            float ps[4] = {0.f, 0.f, 0.f, 0.f};
#pragma unroll
            for (int j = 0; j < 16; j++) { x[j] = ex2(fmaf(x[j], c, -mc)); ps[j & 3] += x[j]; }
            return (ps[0] + ps[1]) + (ps[2] + ps[3]);
        };
        auto make_frag = [&](const float (&x)[16], float f, uint32_t (&pa)[8][4]) {
#pragma unroll
            for (int j = 0; j < 8; j++) {
                const uint32_t pk = pack_bf16(x[2 * j] * f, x[2 * j + 1] * f);
                pa[j][0] = pk & 0xFFFFu;
                pa[j][1] = pk << 16;
                pa[j][2] = pk >> 16;
                pa[j][3] = pk & 0xFFFF0000u;
#pragma unroll
                for (int r = 0; r < 4; r++) asm volatile("" : "+r"(pa[j][r]));
            }
        };
        auto scale_o = [&](float f) {
#pragma unroll
            for (int i = 0; i < 32; i++) { o[i] *= f; asm volatile("" : "+f"(o[i])); }
        };
        auto pv_issue = [&](const uint32_t (&pa)[8][4], int slot, int phase) {
            mbar_wait(full0 + 8 * slot, phase);
            const uint64_t dv = make_desc(tiles + slot * kTileBytes);
            wg_fence();
#pragma unroll
            for (int j = 0; j < 8; j++) wgmma_pv(o, pa[j], dv + j * (2048 >> 4));
            wg_commit();
        };

#pragma unroll 1
        for (int run = 0; run < kNumTiles / kRun - 1; run++) {
#pragma unroll
            for (int i = 0; i < kRun; i++) qk_step(sq[i]);
            const float alpha = ex2((mo - m) * c);
            mo = m;
            l *= alpha;
            scale_o(alpha);
#pragma unroll
            for (int i = 0; i < kRun; i++) {
                uint32_t pa[8][4];
                l += expo(sq[i]);
                make_frag(sq[i], 1.f, pa);
                pv_issue(pa, s, ph);
                wg_wait();
                if (lane == 0) mbar_arrive(empty0 + 8 * s);
                if (++s == kStages) { s = 0; ph ^= 1; }
            }
        }
#pragma unroll
        for (int i = 0; i < kRun; i++) qk_step(sq[i]);
        const float alpha = ex2((mo - m) * c);
        l *= alpha;
#pragma unroll
        for (int i = 0; i < kRun; i++) l += expo(sq[i]);
        l += __shfl_xor_sync(0xffffffffu, l, 1);
        l += __shfl_xor_sync(0xffffffffu, l, 2);
        float inv;
        asm("rcp.approx.ftz.f32 %0, %1;" : "=f"(inv) : "f"(l));
        scale_o(alpha * inv);
        uint32_t pa[kRun][8][4];
#pragma unroll
        for (int i = 0; i < kRun; i++) make_frag(sq[i], inv, pa[i]);
        uint32_t st_addr[4], ld_addr[4];
#pragma unroll
        for (int h = 0; h < 4; h++) {
            const uint32_t stage = tiles + kStages * kTileBytes + warp * 2048;
            st_addr[h] = stage + (lane & 7) * 256 + (((4 * h + (lane >> 3)) ^ (lane & 7)) << 4);
            ld_addr[h] = stage + (lane >> 4) * 256 + h * 512 + (((lane & 15) ^ (2 * h + (lane >> 4))) << 4);
        }
        {
            uint32_t x = st_addr[0] | st_addr[1] | st_addr[2] | st_addr[3] | ld_addr[0] | ld_addr[1] | ld_addr[2] | ld_addr[3];
#pragma unroll
            for (int i = 0; i < 32; i++) x |= __float_as_uint(o[i]);
#pragma unroll
            for (int i = 0; i < kRun; i++)
#pragma unroll
                for (int j = 0; j < 8; j++) x |= pa[i][j][0] | pa[i][j][1] | pa[i][j][2] | pa[i][j][3];
            s_pace[2] = x;
        }
#pragma unroll
        for (int i = 0; i < kRun; i++) {
            const int j = kChunks - kRun + i;
            pv_issue(pa[i], j % kStages, (j / kStages) & 1);
        }
        wg_wait();
#pragma unroll
        for (int i = 0; i < 32; i++) asm volatile("" : "+f"(o[i]) :: "memory");
#pragma unroll
        for (int h = 0; h < 4; h++) {
            const int e = (h >> 1) * 2, i0 = (h & 1) * 4;
            asm volatile("stmatrix.sync.aligned.m8n8.x4.shared.b16 [%0], {%1,%2,%3,%4};"
                         ::"r"(st_addr[h]),
                           "r"(pack_bf16(o[4 * i0 + e], o[4 * i0 + e + 1])), "r"(pack_bf16(o[4 * i0 + 4 + e], o[4 * i0 + 5 + e])),
                           "r"(pack_bf16(o[4 * i0 + 8 + e], o[4 * i0 + 9 + e])), "r"(pack_bf16(o[4 * i0 + 12 + e], o[4 * i0 + 13 + e])) : "memory");
        }
        __syncwarp();
#pragma unroll
        for (int h = 0; h < 4; h++) {
            uint32_t a0, a1, a2, a3;
            asm volatile("ld.shared.v4.b32 {%0,%1,%2,%3}, [%4];" : "=r"(a0), "=r"(a1), "=r"(a2), "=r"(a3)
                         : "r"(ld_addr[h]) : "memory");
            asm volatile("st.global.v4.u32 [%0], {%1,%2,%3,%4};" ::"l"(op + h * 2 * (kD / 8)), "r"(a0), "r"(a1), "r"(a2), "r"(a3) : "memory");
        }
    }
}

typedef CUresult (*EncodeTiledFn)(CUtensorMap*, CUtensorMapDataType, cuuint32_t, void*, const cuuint64_t*,
                                  const cuuint64_t*, const cuuint32_t*, const cuuint32_t*, CUtensorMapInterleave,
                                  CUtensorMapSwizzle, CUtensorMapL2promotion, CUtensorMapFloatOOBfill);

void make_map(EncodeTiledFn enc, CUtensorMap* tm, const void* base) {
    const cuuint64_t dims[2] = {64, (cuuint64_t)kB * kHkv * kSk * 2};
    const cuuint64_t strides[1] = {128};
    const cuuint32_t box[2] = {64, (cuuint32_t)kTileUnits};
    const cuuint32_t estr[2] = {1, 1};
    enc(tm, CU_TENSOR_MAP_DATA_TYPE_BFLOAT16, 2, const_cast<void*>(base), dims, strides, box, estr,
        CU_TENSOR_MAP_INTERLEAVE_NONE, CU_TENSOR_MAP_SWIZZLE_128B, CU_TENSOR_MAP_L2_PROMOTION_NONE,
        CU_TENSOR_MAP_FLOAT_OOB_FILL_NONE);
}

}

extern "C" void kernel_launch(void* const* d_in, const int* in_sizes, int n_in, void* d_out, int out_size) {
    (void)in_sizes; (void)n_in; (void)out_size;
    static EncodeTiledFn enc = nullptr;
    if (!enc) {
        cudaDriverEntryPointQueryResult qr;
        cudaGetDriverEntryPoint("cuTensorMapEncodeTiled", (void**)&enc, cudaEnableDefault, &qr);
        cudaFuncSetAttribute(gqa_decode_kernel, cudaFuncAttributeMaxDynamicSharedMemorySize, kSmemBytes);
    }
    CUtensorMap tmK, tmV;
    make_map(enc, &tmK, d_in[1]);
    make_map(enc, &tmV, d_in[2]);
    gqa_decode_kernel<<<kNumCta, kThreads, kSmemBytes>>>(tmK, tmV, (const __nv_bfloat16*)d_in[0], (__nv_bfloat16*)d_out);
}
```

```cpp
#include <cuda_runtime.h>
#include <cuda_bf16.h>
#include <cuda.h>
#include <stdint.h>

namespace {

constexpr int kB = 32, kHq = 32, kHkv = 4, kSq = 4, kSk = 2048, kD = 128;
constexpr int kRowsQ = (kHq / kHkv) * kSq;
constexpr int kNumCta = kB * kHkv;
constexpr int kTileRows = 64;
constexpr int kTileBytes = kTileRows * kD * 2;
constexpr int kTileUnits = kTileRows * 2;
constexpr int kNumTiles = kSk / kTileRows;
constexpr int kChunks = 2 * kNumTiles;
constexpr int kRun = 4;
#define NSTAGE 10
#define BIAS 704
#define WMIN 3
#define WMAX 7
constexpr int kStages = NSTAGE;
constexpr int kWindow = 4;
constexpr int kCredit = BIAS;
constexpr int kMinFlight = WMIN, kMaxFlight = WMAX;
constexpr uint32_t kQDelay = 450;
constexpr int kThreads = 128 + 64;
constexpr int kSmemBytes = kStages * kTileBytes + kRowsQ * kD * 2 + 1024;

__device__ __forceinline__ uint32_t smem_u32(const void* p) { return (uint32_t)__cvta_generic_to_shared(p); }
__device__ __forceinline__ void mbar_init(uint32_t bar, uint32_t cnt) {
    asm volatile("mbarrier.init.shared::cta.b64 [%0], %1;" ::"r"(bar), "r"(cnt) : "memory");
}
__device__ __forceinline__ void mbar_expect_tx(uint32_t bar, uint32_t bytes) {
    asm volatile("mbarrier.arrive.expect_tx.shared::cta.b64 _, [%0], %1;" ::"r"(bar), "r"(bytes) : "memory");
}
__device__ __forceinline__ void mbar_arrive(uint32_t bar) {
    asm volatile("mbarrier.arrive.shared::cta.b64 _, [%0];" ::"r"(bar) : "memory");
}
__device__ __forceinline__ void mbar_wait(uint32_t bar, uint32_t parity) {
    asm volatile(
        "{\n"
        ".reg .pred p;\n"
        "WAIT_LOOP:\n"
        "mbarrier.try_wait.parity.shared::cta.b64 p, [%0], %1;\n"
        "@p bra WAIT_DONE;\n"
        "bra WAIT_LOOP;\n"
        "WAIT_DONE:\n"
        "}\n" ::"r"(bar), "r"(parity) : "memory");
}
__device__ __forceinline__ bool mbar_test(uint32_t bar, uint32_t parity) {
    uint32_t ok;
    asm volatile("{\n.reg .pred p;\nmbarrier.test_wait.parity.shared::cta.b64 p, [%1], %2;\nselp.u32 %0, 1, 0, p;\n}\n"
                 : "=r"(ok) : "r"(bar), "r"(parity) : "memory");
    return ok != 0;
}
__device__ __forceinline__ void tma_load(uint32_t dst, const CUtensorMap* tm, uint32_t bar, int unit) {
    asm volatile(
        "cp.async.bulk.tensor.2d.shared::cluster.global.mbarrier::complete_tx::bytes [%0], [%1, {%3, %4}], [%2];"
        ::"r"(dst), "l"(tm), "r"(bar), "r"(0), "r"(unit) : "memory");
}
__device__ __forceinline__ void wg_fence() { asm volatile("wgmma.fence.sync.aligned;" ::: "memory"); }
__device__ __forceinline__ void wg_commit() { asm volatile("wgmma.commit_group.sync.aligned;" ::: "memory"); }
__device__ __forceinline__ void wg_wait() { asm volatile("wgmma.wait_group.sync.aligned 0;" ::: "memory"); }

__device__ __forceinline__ uint64_t make_desc(uint32_t addr) {
    return (uint64_t)((addr & 0x3FFFF) >> 4) | ((uint64_t)1 << 16) | ((uint64_t)(1024 >> 4) << 32) | ((uint64_t)1 << 62);
}

__device__ __forceinline__ void wgmma_qk(float (&d)[64], const uint32_t (&a)[4], uint64_t desc, int scale_d) {
    asm volatile(
        "{\n.reg .pred p;\nsetp.ne.b32 p, %69, 0;\n"
        "wgmma.mma_async.sync.aligned.m64n128k16.f32.bf16.bf16 "
        "{%0,%1,%2,%3,%4,%5,%6,%7,%8,%9,%10,%11,%12,%13,%14,%15,"
        "%16,%17,%18,%19,%20,%21,%22,%23,%24,%25,%26,%27,%28,%29,%30,%31,"
        "%32,%33,%34,%35,%36,%37,%38,%39,%40,%41,%42,%43,%44,%45,%46,%47,"
        "%48,%49,%50,%51,%52,%53,%54,%55,%56,%57,%58,%59,%60,%61,%62,%63},"
        "{%64,%65,%66,%67}, %68, p, 1, 1, 0;\n}\n"
        : "+f"(d[0]), "+f"(d[1]), "+f"(d[2]), "+f"(d[3]), "+f"(d[4]), "+f"(d[5]), "+f"(d[6]), "+f"(d[7]),
          "+f"(d[8]), "+f"(d[9]), "+f"(d[10]), "+f"(d[11]), "+f"(d[12]), "+f"(d[13]), "+f"(d[14]), "+f"(d[15]),
          "+f"(d[16]), "+f"(d[17]), "+f"(d[18]), "+f"(d[19]), "+f"(d[20]), "+f"(d[21]), "+f"(d[22]), "+f"(d[23]),
          "+f"(d[24]), "+f"(d[25]), "+f"(d[26]), "+f"(d[27]), "+f"(d[28]), "+f"(d[29]), "+f"(d[30]), "+f"(d[31]),
          "+f"(d[32]), "+f"(d[33]), "+f"(d[34]), "+f"(d[35]), "+f"(d[36]), "+f"(d[37]), "+f"(d[38]), "+f"(d[39]),
          "+f"(d[40]), "+f"(d[41]), "+f"(d[42]), "+f"(d[43]), "+f"(d[44]), "+f"(d[45]), "+f"(d[46]), "+f"(d[47]),
          "+f"(d[48]), "+f"(d[49]), "+f"(d[50]), "+f"(d[51]), "+f"(d[52]), "+f"(d[53]), "+f"(d[54]), "+f"(d[55]),
          "+f"(d[56]), "+f"(d[57]), "+f"(d[58]), "+f"(d[59]), "+f"(d[60]), "+f"(d[61]), "+f"(d[62]), "+f"(d[63])
        : "r"(a[0]), "r"(a[1]), "r"(a[2]), "r"(a[3]), "l"(desc), "r"(scale_d));
}

__device__ __forceinline__ void wgmma_pv(float (&d)[32], const uint32_t (&a)[4], uint64_t desc) {
    asm volatile(
        "wgmma.mma_async.sync.aligned.m64n64k16.f32.bf16.bf16 "
        "{%0,%1,%2,%3,%4,%5,%6,%7,%8,%9,%10,%11,%12,%13,%14,%15,"
        "%16,%17,%18,%19,%20,%21,%22,%23,%24,%25,%26,%27,%28,%29,%30,%31},"
        "{%32,%33,%34,%35}, %36, 1, 1, 1, 1;\n"
        : "+f"(d[0]), "+f"(d[1]), "+f"(d[2]), "+f"(d[3]), "+f"(d[4]), "+f"(d[5]), "+f"(d[6]), "+f"(d[7]),
          "+f"(d[8]), "+f"(d[9]), "+f"(d[10]), "+f"(d[11]), "+f"(d[12]), "+f"(d[13]), "+f"(d[14]), "+f"(d[15]),
          "+f"(d[16]), "+f"(d[17]), "+f"(d[18]), "+f"(d[19]), "+f"(d[20]), "+f"(d[21]), "+f"(d[22]), "+f"(d[23]),
          "+f"(d[24]), "+f"(d[25]), "+f"(d[26]), "+f"(d[27]), "+f"(d[28]), "+f"(d[29]), "+f"(d[30]), "+f"(d[31])
        : "r"(a[0]), "r"(a[1]), "r"(a[2]), "r"(a[3]), "l"(desc));
}

__device__ __forceinline__ uint32_t ldg_u32(const uint32_t* p) {
    uint32_t v; asm volatile("ld.global.u32 %0, [%1];" : "=r"(v) : "l"(p) : "memory"); return v;
}
__device__ __forceinline__ float ex2(float x) { float y; asm("ex2.approx.ftz.f32 %0, %1;" : "=f"(y) : "f"(x)); return y; }
__device__ __forceinline__ uint32_t pack_bf16(float lo, float hi) {
    uint32_t r; asm("cvt.rn.bf16x2.f32 %0, %1, %2;" : "=r"(r) : "f"(hi), "f"(lo)); return r;
}

__device__ unsigned int g_landed;

__device__ __forceinline__ void chunk_of(int j, bool& is_v, int& tile) {
    is_v = (j / kRun) & 1;
    tile = (j / (2 * kRun)) * kRun + j % kRun;
}

__global__ void __launch_bounds__(kThreads, 1)
gqa_decode_kernel(const __grid_constant__ CUtensorMap tmK, const __grid_constant__ CUtensorMap tmV,
                  const __nv_bfloat16* __restrict__ q, __nv_bfloat16* __restrict__ out) {
    extern __shared__ uint8_t smem_raw[];
    __shared__ __align__(8) uint64_t bars[2 * kStages];
    __shared__ volatile int s_pace[3];
    const int bh = blockIdx.x;
    const int unit0 = bh * (kSk * 2);
    const int lane = threadIdx.x & 31;

    if (threadIdx.x == 128) {
        const uint32_t tiles = (smem_u32(smem_raw) + 1023u) & ~1023u;
        const uint32_t full0 = smem_u32(&bars[0]), empty0 = full0 + 8 * kStages;
#pragma unroll
        for (int j = 0; j < kWindow; j++) mbar_init(full0 + 8 * j, 1);
        asm volatile("fence.mbarrier_init.release.cluster;" ::: "memory");
#pragma unroll
        for (int j = 0; j < kWindow; j++) {
            bool is_v; int tile;
            chunk_of(j, is_v, tile);
            mbar_expect_tx(full0 + 8 * j, kTileBytes);
            tma_load(tiles + j * kTileBytes, is_v ? &tmV : &tmK, full0 + 8 * j, unit0 + tile * kTileUnits);
        }
#pragma unroll
        for (int s = kWindow; s < kStages; s++) mbar_init(full0 + 8 * s, 1);
#pragma unroll
        for (int s = 0; s < kStages; s++) mbar_init(empty0 + 8 * s, 4);
        asm volatile("fence.mbarrier_init.release.cluster;" ::: "memory");
        s_pace[0] = 0; s_pace[1] = 0;
    }

    if (threadIdx.x >= 160) {
        asm volatile("bar.sync 2, 64;" ::: "memory");
        if (lane == 0) {
            int best = 0;
            while (!s_pace[1]) {
                unsigned v;
                asm volatile("ld.relaxed.gpu.global.u32 %0, [%1];" : "=r"(v) : "l"(&g_landed) : "memory");
                best = max(best, (int)(v & (kNumCta * kChunks - 1)));
                s_pace[0] = best;
            }
        }
    } else if (threadIdx.x >= 128) {
        const uint32_t tiles = (smem_u32(smem_raw) + 1023u) & ~1023u;
        const uint32_t full0 = smem_u32(&bars[0]), empty0 = full0 + 8 * kStages;
        __syncwarp();
        asm volatile("bar.arrive 1, 160;" ::: "memory");
        asm volatile("bar.arrive 2, 64;" ::: "memory");
        bool inflight = lane < kWindow;
        uint32_t fph = 0;
        int issued = kWindow, arrived = 0, slot = kWindow % kStages, eph = (kWindow / kStages) & 1;
        while (issued < kChunks) {
            const bool rdy = inflight && mbar_test(full0 + 8 * lane, fph);
            const int nrdy = __popc(__ballot_sync(0xffffffffu, rdy));
            arrived += nrdy;
            if (nrdy && lane == 0) asm volatile("red.relaxed.gpu.global.add.u32 [%0], %1;" ::"l"(&g_landed), "r"(nrdy) : "memory");
            const int credit = s_pace[0] + kCredit - bh;
            if (rdy) { inflight = false; fph ^= 1; }
            while (issued < kChunks &&
                   (issued - arrived < kMinFlight || (issued - arrived < kMaxFlight && issued * kNumCta <= credit))) {
                if (!mbar_test(empty0 + 8 * slot, eph ^ 1)) break;
                if (lane == slot) {
                    bool is_v; int tile;
                    chunk_of(issued, is_v, tile);
                    mbar_expect_tx(full0 + 8 * slot, kTileBytes);
                    tma_load(tiles + slot * kTileBytes, is_v ? &tmV : &tmK, full0 + 8 * slot, unit0 + tile * kTileUnits);
                    inflight = true;
                }
                issued++;
                if (++slot == kStages) { slot = 0; eph ^= 1; }
            }
        }
        if (lane == 0) {
            s_pace[1] = 1;
            asm volatile("red.relaxed.gpu.global.add.u32 [%0], %1;" ::"l"(&g_landed), "r"(kChunks - arrived) : "memory");
        }
    } else {
        const int warp = __shfl_sync(0xffffffffu, threadIdx.x >> 5, 0);
        const uint32_t tiles = __shfl_sync(0xffffffffu, (smem_u32(smem_raw) + 1023u) & ~1023u, 0);
        const uint32_t full0 = __shfl_sync(0xffffffffu, smem_u32(&bars[0]), 0), empty0 = full0 + 8 * kStages;
        const int g = lane >> 2, t = lane & 3;
        {
            uint32_t t0, t1;
            asm volatile("mov.u32 %0, %clock;" : "=r"(t0) :: "memory");
            do { asm volatile("mov.u32 %0, %clock;" : "=r"(t1) :: "memory"); } while (t1 - t0 < kQDelay);
        }
        uint32_t qa[4][4];
        {
            const uint32_t* qp = reinterpret_cast<const uint32_t*>(q + (size_t)(bh * kRowsQ + warp * 8 + g) * kD) + t;
#pragma unroll
            for (int kk = 0; kk < 4; kk++) {
                qa[kk][0] = ldg_u32(qp + kk * 8);
                qa[kk][1] = ldg_u32(qp + 32 + kk * 8);
                qa[kk][2] = ldg_u32(qp + kk * 8 + 4);
                qa[kk][3] = ldg_u32(qp + 32 + kk * 8 + 4);
            }
        }
        uint4* op = reinterpret_cast<uint4*>(out + (size_t)(bh * kRowsQ + warp * 8 + (lane >> 4)) * kD) + (lane & 15);
        asm volatile("add.u64 %0, %0, 0;" : "+l"(op));
        float o[32];
#pragma unroll
        for (int i = 0; i < 32; i++) o[i] = 0.f;
        float m = -INFINITY;
        float mo = -INFINITY;
        float l = 0.f;
        float sq[kRun][16];
        const float c = 0.08838834764831845f * 1.4426950408889634f;
        asm volatile("bar.sync 1, 160;" ::: "memory");

        int s = 0, ph = 0;

        auto qk_step = [&](float (&dst)[16]) {
            float sc[64];
            mbar_wait(full0 + 8 * s, ph);
            const uint64_t dk = make_desc(tiles + s * kTileBytes);
            wg_fence();
#pragma unroll
            for (int kk = 0; kk < 4; kk++) wgmma_qk(sc, qa[kk], dk + kk * 2, kk);
            wg_commit();
            wg_wait();
            if (lane == 0) mbar_arrive(empty0 + 8 * s);
            if (++s == kStages) { s = 0; ph ^= 1; }
#pragma unroll
            for (int i = 0; i < 64; i++) asm volatile("" : "+f"(sc[i]) :: "memory");
#pragma unroll
            for (int i = 0; i < 16; i++) dst[i] = sc[4 * i] + sc[4 * i + 3];
            float mx[4];
#pragma unroll
            for (int i = 0; i < 4; i++) mx[i] = fmaxf(fmaxf(dst[4 * i], dst[4 * i + 1]), fmaxf(dst[4 * i + 2], dst[4 * i + 3]));
            float mm = fmaxf(fmaxf(mx[0], mx[1]), fmaxf(mx[2], mx[3]));
            mm = fmaxf(mm, __shfl_xor_sync(0xffffffffu, mm, 1));
            mm = fmaxf(mm, __shfl_xor_sync(0xffffffffu, mm, 2));
            m = fmaxf(m, mm);
        };
        auto expo = [&](float (&x)[16]) {
            const float mc = m * c;
            float ps[4] = {0.f, 0.f, 0.f, 0.f};
#pragma unroll
            for (int j = 0; j < 16; j++) { x[j] = ex2(fmaf(x[j], c, -mc)); ps[j & 3] += x[j]; }
            return (ps[0] + ps[1]) + (ps[2] + ps[3]);
        };
        auto make_frag = [&](const float (&x)[16], float f, uint32_t (&pa)[8][4]) {
#pragma unroll
            for (int j = 0; j < 8; j++) {
                const uint32_t pk = pack_bf16(x[2 * j] * f, x[2 * j + 1] * f);
                pa[j][0] = pk & 0xFFFFu;
                pa[j][1] = pk << 16;
                pa[j][2] = pk >> 16;
                pa[j][3] = pk & 0xFFFF0000u;
#pragma unroll
                for (int r = 0; r < 4; r++) asm volatile("" : "+r"(pa[j][r]));
            }
        };
        auto scale_o = [&](float f) {
#pragma unroll
            for (int i = 0; i < 32; i++) { o[i] *= f; asm volatile("" : "+f"(o[i])); }
        };
        auto pv_issue = [&](const uint32_t (&pa)[8][4], int slot, int phase) {
            mbar_wait(full0 + 8 * slot, phase);
            const uint64_t dv = make_desc(tiles + slot * kTileBytes);
            wg_fence();
#pragma unroll
            for (int j = 0; j < 8; j++) wgmma_pv(o, pa[j], dv + j * (2048 >> 4));
            wg_commit();
        };

#pragma unroll 1
        for (int run = 0; run < kNumTiles / kRun - 1; run++) {
#pragma unroll
            for (int i = 0; i < kRun; i++) qk_step(sq[i]);
            const float alpha = ex2((mo - m) * c);
            mo = m;
            l *= alpha;
            scale_o(alpha);
#pragma unroll
            for (int i = 0; i < kRun; i++) {
                uint32_t pa[8][4];
                l += expo(sq[i]);
                make_frag(sq[i], 1.f, pa);
                pv_issue(pa, s, ph);
                wg_wait();
                if (lane == 0) mbar_arrive(empty0 + 8 * s);
                if (++s == kStages) { s = 0; ph ^= 1; }
            }
        }
#pragma unroll
        for (int i = 0; i < kRun; i++) qk_step(sq[i]);
        const float alpha = ex2((mo - m) * c);
        l *= alpha;
#pragma unroll
        for (int i = 0; i < kRun; i++) l += expo(sq[i]);
        l += __shfl_xor_sync(0xffffffffu, l, 1);
        l += __shfl_xor_sync(0xffffffffu, l, 2);
        float inv;
        asm("rcp.approx.ftz.f32 %0, %1;" : "=f"(inv) : "f"(l));
        scale_o(alpha * inv);
        uint32_t pa[kRun][8][4];
#pragma unroll
        for (int i = 0; i < kRun; i++) make_frag(sq[i], inv, pa[i]);
        uint32_t st_addr[4], ld_addr[4];
#pragma unroll
        for (int h = 0; h < 4; h++) {
            const uint32_t stage = tiles + kStages * kTileBytes + warp * 2048;
            st_addr[h] = stage + (lane & 7) * 256 + (((4 * h + (lane >> 3)) ^ (lane & 7)) << 4);
            ld_addr[h] = stage + (lane >> 4) * 256 + h * 512 + (((lane & 15) ^ (2 * h + (lane >> 4))) << 4);
        }
        {
            uint32_t x = st_addr[0] | st_addr[1] | st_addr[2] | st_addr[3] | ld_addr[0] | ld_addr[1] | ld_addr[2] | ld_addr[3];
#pragma unroll
            for (int i = 0; i < 32; i++) x |= __float_as_uint(o[i]);
#pragma unroll
            for (int i = 0; i < kRun; i++)
#pragma unroll
                for (int j = 0; j < 8; j++) x |= pa[i][j][0] | pa[i][j][1] | pa[i][j][2] | pa[i][j][3];
            s_pace[2] = x;
        }
#pragma unroll
        for (int i = 0; i < kRun; i++) {
            const int j = kChunks - kRun + i;
            pv_issue(pa[i], j % kStages, (j / kStages) & 1);
        }
        wg_wait();
#pragma unroll
        for (int i = 0; i < 32; i++) asm volatile("" : "+f"(o[i]) :: "memory");
#pragma unroll
        for (int h = 0; h < 4; h++) {
            const int e = (h >> 1) * 2, i0 = (h & 1) * 4;
            asm volatile("stmatrix.sync.aligned.m8n8.x4.shared.b16 [%0], {%1,%2,%3,%4};"
                         ::"r"(st_addr[h]),
                           "r"(pack_bf16(o[4 * i0 + e], o[4 * i0 + e + 1])), "r"(pack_bf16(o[4 * i0 + 4 + e], o[4 * i0 + 5 + e])),
                           "r"(pack_bf16(o[4 * i0 + 8 + e], o[4 * i0 + 9 + e])), "r"(pack_bf16(o[4 * i0 + 12 + e], o[4 * i0 + 13 + e])) : "memory");
        }
        __syncwarp();
#pragma unroll
        for (int h = 0; h < 4; h++) {
            uint32_t a0, a1, a2, a3;
            asm volatile("ld.shared.v4.b32 {%0,%1,%2,%3}, [%4];" : "=r"(a0), "=r"(a1), "=r"(a2), "=r"(a3)
                         : "r"(ld_addr[h]) : "memory");
            asm volatile("st.global.v4.u32 [%0], {%1,%2,%3,%4};" ::"l"(op + h * 2 * (kD / 8)), "r"(a0), "r"(a1), "r"(a2), "r"(a3) : "memory");
        }
    }
}

typedef CUresult (*EncodeTiledFn)(CUtensorMap*, CUtensorMapDataType, cuuint32_t, void*, const cuuint64_t*,
                                  const cuuint64_t*, const cuuint32_t*, const cuuint32_t*, CUtensorMapInterleave,
                                  CUtensorMapSwizzle, CUtensorMapL2promotion, CUtensorMapFloatOOBfill);

void make_map(EncodeTiledFn enc, CUtensorMap* tm, const void* base) {
    const cuuint64_t dims[2] = {64, (cuuint64_t)kB * kHkv * kSk * 2};
    const cuuint64_t strides[1] = {128};
    const cuuint32_t box[2] = {64, (cuuint32_t)kTileUnits};
    const cuuint32_t estr[2] = {1, 1};
    enc(tm, CU_TENSOR_MAP_DATA_TYPE_BFLOAT16, 2, const_cast<void*>(base), dims, strides, box, estr,
        CU_TENSOR_MAP_INTERLEAVE_NONE, CU_TENSOR_MAP_SWIZZLE_128B, CU_TENSOR_MAP_L2_PROMOTION_NONE,
        CU_TENSOR_MAP_FLOAT_OOB_FILL_NONE);
}

}

extern "C" void kernel_launch(void* const* d_in, const int* in_sizes, int n_in, void* d_out, int out_size) {
    (void)in_sizes; (void)n_in; (void)out_size;
    static EncodeTiledFn enc = nullptr;
    if (!enc) {
        cudaDriverEntryPointQueryResult qr;
        cudaGetDriverEntryPoint("cuTensorMapEncodeTiled", (void**)&enc, cudaEnableDefault, &qr);
        cudaFuncSetAttribute(gqa_decode_kernel, cudaFuncAttributeMaxDynamicSharedMemorySize, kSmemBytes);
    }
    CUtensorMap tmK, tmV;
    make_map(enc, &tmK, d_in[1]);
    make_map(enc, &tmV, d_in[2]);
    gqa_decode_kernel<<<kNumCta, kThreads, kSmemBytes>>>(tmK, tmV, (const __nv_bfloat16*)d_in[0], (__nv_bfloat16*)d_out);
}
```

```cpp
#include <cuda_runtime.h>
#include <cuda_bf16.h>
#include <cuda.h>
#include <stdint.h>

namespace {

constexpr int kB = 32, kHq = 32, kHkv = 4, kSq = 4, kSk = 2048, kD = 128;
constexpr int kRowsQ = (kHq / kHkv) * kSq;
constexpr int kNumCta = kB * kHkv;
constexpr int kTileRows = 64;
constexpr int kTileBytes = kTileRows * kD * 2;
constexpr int kTileUnits = kTileRows * 2;
constexpr int kNumTiles = kSk / kTileRows;
constexpr int kChunks = 2 * kNumTiles;
constexpr int kRun = 4;
constexpr int kStages = 10;
constexpr int kWindow = 4;
constexpr int kCredit = 704;
constexpr int kTaperFrom = 52, kTaperStep = 24;
constexpr int kMinFlight = 3, kMaxFlight = 7;
constexpr uint32_t kQDelay = 450;
constexpr int kThreads = 128 + 64;
constexpr int kSmemBytes = kStages * kTileBytes + kRowsQ * kD * 2 + 1024;

__device__ __forceinline__ uint32_t smem_u32(const void* p) { return (uint32_t)__cvta_generic_to_shared(p); }
__device__ __forceinline__ void mbar_init(uint32_t bar, uint32_t cnt) {
    asm volatile("mbarrier.init.shared::cta.b64 [%0], %1;" ::"r"(bar), "r"(cnt) : "memory");
}
__device__ __forceinline__ void mbar_expect_tx(uint32_t bar, uint32_t bytes) {
    asm volatile("mbarrier.arrive.expect_tx.shared::cta.b64 _, [%0], %1;" ::"r"(bar), "r"(bytes) : "memory");
}
__device__ __forceinline__ void mbar_arrive(uint32_t bar) {
    asm volatile("mbarrier.arrive.shared::cta.b64 _, [%0];" ::"r"(bar) : "memory");
}
__device__ __forceinline__ void mbar_wait(uint32_t bar, uint32_t parity) {
    asm volatile(
        "{\n"
        ".reg .pred p;\n"
        "WAIT_LOOP:\n"
        "mbarrier.try_wait.parity.shared::cta.b64 p, [%0], %1;\n"
        "@p bra WAIT_DONE;\n"
        "bra WAIT_LOOP;\n"
        "WAIT_DONE:\n"
        "}\n" ::"r"(bar), "r"(parity) : "memory");
}
__device__ __forceinline__ bool mbar_test(uint32_t bar, uint32_t parity) {
    uint32_t ok;
    asm volatile("{\n.reg .pred p;\nmbarrier.test_wait.parity.shared::cta.b64 p, [%1], %2;\nselp.u32 %0, 1, 0, p;\n}\n"
                 : "=r"(ok) : "r"(bar), "r"(parity) : "memory");
    return ok != 0;
}
__device__ __forceinline__ void tma_load(uint32_t dst, const CUtensorMap* tm, uint32_t bar, int unit) {
    asm volatile(
        "cp.async.bulk.tensor.2d.shared::cluster.global.mbarrier::complete_tx::bytes [%0], [%1, {%3, %4}], [%2];"
        ::"r"(dst), "l"(tm), "r"(bar), "r"(0), "r"(unit) : "memory");
}
__device__ __forceinline__ void wg_fence() { asm volatile("wgmma.fence.sync.aligned;" ::: "memory"); }
__device__ __forceinline__ void wg_commit() { asm volatile("wgmma.commit_group.sync.aligned;" ::: "memory"); }
__device__ __forceinline__ void wg_wait() { asm volatile("wgmma.wait_group.sync.aligned 0;" ::: "memory"); }

__device__ __forceinline__ uint64_t make_desc(uint32_t addr) {
    return (uint64_t)((addr & 0x3FFFF) >> 4) | ((uint64_t)1 << 16) | ((uint64_t)(1024 >> 4) << 32) | ((uint64_t)1 << 62);
}

__device__ __forceinline__ void wgmma_qk(float (&d)[64], const uint32_t (&a)[4], uint64_t desc, int scale_d) {
    asm volatile(
        "{\n.reg .pred p;\nsetp.ne.b32 p, %69, 0;\n"
        "wgmma.mma_async.sync.aligned.m64n128k16.f32.bf16.bf16 "
        "{%0,%1,%2,%3,%4,%5,%6,%7,%8,%9,%10,%11,%12,%13,%14,%15,"
        "%16,%17,%18,%19,%20,%21,%22,%23,%24,%25,%26,%27,%28,%29,%30,%31,"
        "%32,%33,%34,%35,%36,%37,%38,%39,%40,%41,%42,%43,%44,%45,%46,%47,"
        "%48,%49,%50,%51,%52,%53,%54,%55,%56,%57,%58,%59,%60,%61,%62,%63},"
        "{%64,%65,%66,%67}, %68, p, 1, 1, 0;\n}\n"
        : "+f"(d[0]), "+f"(d[1]), "+f"(d[2]), "+f"(d[3]), "+f"(d[4]), "+f"(d[5]), "+f"(d[6]), "+f"(d[7]),
          "+f"(d[8]), "+f"(d[9]), "+f"(d[10]), "+f"(d[11]), "+f"(d[12]), "+f"(d[13]), "+f"(d[14]), "+f"(d[15]),
          "+f"(d[16]), "+f"(d[17]), "+f"(d[18]), "+f"(d[19]), "+f"(d[20]), "+f"(d[21]), "+f"(d[22]), "+f"(d[23]),
          "+f"(d[24]), "+f"(d[25]), "+f"(d[26]), "+f"(d[27]), "+f"(d[28]), "+f"(d[29]), "+f"(d[30]), "+f"(d[31]),
          "+f"(d[32]), "+f"(d[33]), "+f"(d[34]), "+f"(d[35]), "+f"(d[36]), "+f"(d[37]), "+f"(d[38]), "+f"(d[39]),
          "+f"(d[40]), "+f"(d[41]), "+f"(d[42]), "+f"(d[43]), "+f"(d[44]), "+f"(d[45]), "+f"(d[46]), "+f"(d[47]),
          "+f"(d[48]), "+f"(d[49]), "+f"(d[50]), "+f"(d[51]), "+f"(d[52]), "+f"(d[53]), "+f"(d[54]), "+f"(d[55]),
          "+f"(d[56]), "+f"(d[57]), "+f"(d[58]), "+f"(d[59]), "+f"(d[60]), "+f"(d[61]), "+f"(d[62]), "+f"(d[63])
        : "r"(a[0]), "r"(a[1]), "r"(a[2]), "r"(a[3]), "l"(desc), "r"(scale_d));
}

__device__ __forceinline__ void wgmma_pv(float (&d)[32], const uint32_t (&a)[4], uint64_t desc) {
    asm volatile(
        "wgmma.mma_async.sync.aligned.m64n64k16.f32.bf16.bf16 "
        "{%0,%1,%2,%3,%4,%5,%6,%7,%8,%9,%10,%11,%12,%13,%14,%15,"
        "%16,%17,%18,%19,%20,%21,%22,%23,%24,%25,%26,%27,%28,%29,%30,%31},"
        "{%32,%33,%34,%35}, %36, 1, 1, 1, 1;\n"
        : "+f"(d[0]), "+f"(d[1]), "+f"(d[2]), "+f"(d[3]), "+f"(d[4]), "+f"(d[5]), "+f"(d[6]), "+f"(d[7]),
          "+f"(d[8]), "+f"(d[9]), "+f"(d[10]), "+f"(d[11]), "+f"(d[12]), "+f"(d[13]), "+f"(d[14]), "+f"(d[15]),
          "+f"(d[16]), "+f"(d[17]), "+f"(d[18]), "+f"(d[19]), "+f"(d[20]), "+f"(d[21]), "+f"(d[22]), "+f"(d[23]),
          "+f"(d[24]), "+f"(d[25]), "+f"(d[26]), "+f"(d[27]), "+f"(d[28]), "+f"(d[29]), "+f"(d[30]), "+f"(d[31])
        : "r"(a[0]), "r"(a[1]), "r"(a[2]), "r"(a[3]), "l"(desc));
}

__device__ __forceinline__ uint32_t ldg_u32(const uint32_t* p) {
    uint32_t v; asm volatile("ld.global.u32 %0, [%1];" : "=r"(v) : "l"(p) : "memory"); return v;
}
__device__ __forceinline__ float ex2(float x) { float y; asm("ex2.approx.ftz.f32 %0, %1;" : "=f"(y) : "f"(x)); return y; }
__device__ __forceinline__ uint32_t pack_bf16(float lo, float hi) {
    uint32_t r; asm("cvt.rn.bf16x2.f32 %0, %1, %2;" : "=r"(r) : "f"(hi), "f"(lo)); return r;
}

__device__ unsigned int g_landed;

__device__ __forceinline__ void chunk_of(int j, bool& is_v, int& tile) {
    is_v = (j / kRun) & 1;
    tile = (j / (2 * kRun)) * kRun + j % kRun;
}

__global__ void __launch_bounds__(kThreads, 1)
gqa_decode_kernel(const __grid_constant__ CUtensorMap tmK, const __grid_constant__ CUtensorMap tmV,
                  const __nv_bfloat16* __restrict__ q, __nv_bfloat16* __restrict__ out) {
    extern __shared__ uint8_t smem_raw[];
    __shared__ __align__(8) uint64_t bars[2 * kStages];
    __shared__ volatile int s_pace[3];
    const int bh = blockIdx.x;
    const int unit0 = bh * (kSk * 2);
    const int lane = threadIdx.x & 31;

    if (threadIdx.x == 128) {
        const uint32_t tiles = (smem_u32(smem_raw) + 1023u) & ~1023u;
        const uint32_t full0 = smem_u32(&bars[0]), empty0 = full0 + 8 * kStages;
#pragma unroll
        for (int j = 0; j < kWindow; j++) mbar_init(full0 + 8 * j, 1);
        asm volatile("fence.mbarrier_init.release.cluster;" ::: "memory");
#pragma unroll
        for (int j = 0; j < kWindow; j++) {
            bool is_v; int tile;
            chunk_of(j, is_v, tile);
            mbar_expect_tx(full0 + 8 * j, kTileBytes);
            tma_load(tiles + j * kTileBytes, is_v ? &tmV : &tmK, full0 + 8 * j, unit0 + tile * kTileUnits);
        }
#pragma unroll
        for (int s = kWindow; s < kStages; s++) mbar_init(full0 + 8 * s, 1);
#pragma unroll
        for (int s = 0; s < kStages; s++) mbar_init(empty0 + 8 * s, 4);
        asm volatile("fence.mbarrier_init.release.cluster;" ::: "memory");
        s_pace[0] = 0; s_pace[1] = 0;
    }

    if (threadIdx.x >= 160) {
        asm volatile("bar.sync 2, 64;" ::: "memory");
        if (lane == 0) {
            int best = 0;
            while (!s_pace[1]) {
                unsigned v;
                asm volatile("ld.relaxed.gpu.global.u32 %0, [%1];" : "=r"(v) : "l"(&g_landed) : "memory");
                best = max(best, (int)(v & (kNumCta * kChunks - 1)));
                s_pace[0] = best;
            }
        }
    } else if (threadIdx.x >= 128) {
        const uint32_t tiles = (smem_u32(smem_raw) + 1023u) & ~1023u;
        const uint32_t full0 = smem_u32(&bars[0]), empty0 = full0 + 8 * kStages;
        __syncwarp();
        asm volatile("bar.arrive 1, 160;" ::: "memory");
        asm volatile("bar.arrive 2, 64;" ::: "memory");
        bool inflight = lane < kWindow;
        uint32_t fph = 0;
        int issued = kWindow, arrived = 0, slot = kWindow % kStages, eph = (kWindow / kStages) & 1;
        while (issued < kChunks) {
            const bool rdy = inflight && mbar_test(full0 + 8 * lane, fph);
            const int nrdy = __popc(__ballot_sync(0xffffffffu, rdy));
            arrived += nrdy;
            if (nrdy && lane == 0) asm volatile("red.relaxed.gpu.global.add.u32 [%0], %1;" ::"l"(&g_landed), "r"(nrdy) : "memory");
            const int credit = s_pace[0] + kCredit - bh;
            if (rdy) { inflight = false; fph ^= 1; }
            const uint32_t busy = __ballot_sync(0xffffffffu, inflight);
            while (issued < kChunks &&
                   (issued - arrived < kMinFlight ||
                    (issued - arrived < kMaxFlight &&
                     issued * kNumCta + max(0, issued - kTaperFrom) * kTaperStep <= credit))) {
                if (((busy >> slot) & 1) || !mbar_test(empty0 + 8 * slot, eph ^ 1)) break;
                if (lane == slot) {
                    bool is_v; int tile;
                    chunk_of(issued, is_v, tile);
                    mbar_expect_tx(full0 + 8 * slot, kTileBytes);
                    tma_load(tiles + slot * kTileBytes, is_v ? &tmV : &tmK, full0 + 8 * slot, unit0 + tile * kTileUnits);
                    inflight = true;
                }
                issued++;
                if (++slot == kStages) { slot = 0; eph ^= 1; }
            }
        }
        if (lane == 0) {
            s_pace[1] = 1;
            asm volatile("red.relaxed.gpu.global.add.u32 [%0], %1;" ::"l"(&g_landed), "r"(kChunks - arrived) : "memory");
        }
    } else {
        const int warp = __shfl_sync(0xffffffffu, threadIdx.x >> 5, 0);
        const uint32_t tiles = __shfl_sync(0xffffffffu, (smem_u32(smem_raw) + 1023u) & ~1023u, 0);
        const uint32_t full0 = __shfl_sync(0xffffffffu, smem_u32(&bars[0]), 0), empty0 = full0 + 8 * kStages;
        const int g = lane >> 2, t = lane & 3;
        {
            uint32_t t0, t1;
            asm volatile("mov.u32 %0, %clock;" : "=r"(t0) :: "memory");
            do { asm volatile("mov.u32 %0, %clock;" : "=r"(t1) :: "memory"); } while (t1 - t0 < kQDelay);
        }
        uint32_t qa[4][4];
        {
            const uint32_t* qp = reinterpret_cast<const uint32_t*>(q + (size_t)(bh * kRowsQ + warp * 8 + g) * kD) + t;
#pragma unroll
            for (int kk = 0; kk < 4; kk++) {
                qa[kk][0] = ldg_u32(qp + kk * 8);
                qa[kk][1] = ldg_u32(qp + 32 + kk * 8);
                qa[kk][2] = ldg_u32(qp + kk * 8 + 4);
                qa[kk][3] = ldg_u32(qp + 32 + kk * 8 + 4);
            }
        }
        uint4* op = reinterpret_cast<uint4*>(out + (size_t)(bh * kRowsQ + warp * 8 + (lane >> 4)) * kD) + (lane & 15);
        asm volatile("add.u64 %0, %0, 0;" : "+l"(op));
        float o[32];
#pragma unroll
        for (int i = 0; i < 32; i++) o[i] = 0.f;
        float m = -INFINITY;
        float mo = -INFINITY;
        float l = 0.f;
        float sq[kRun][16];
        const float c = 0.08838834764831845f * 1.4426950408889634f;
        asm volatile("bar.sync 1, 160;" ::: "memory");

        int s = 0, ph = 0;

        auto qk_step = [&](float (&dst)[16]) {
            float sc[64];
            mbar_wait(full0 + 8 * s, ph);
            const uint64_t dk = make_desc(tiles + s * kTileBytes);
            wg_fence();
#pragma unroll
            for (int kk = 0; kk < 4; kk++) wgmma_qk(sc, qa[kk], dk + kk * 2, kk);
            wg_commit();
            wg_wait();
            if (lane == 0) mbar_arrive(empty0 + 8 * s);
            if (++s == kStages) { s = 0; ph ^= 1; }
#pragma unroll
            for (int i = 0; i < 64; i++) asm volatile("" : "+f"(sc[i]) :: "memory");
#pragma unroll
            for (int i = 0; i < 16; i++) dst[i] = sc[4 * i] + sc[4 * i + 3];
            float mx[4];
#pragma unroll
            for (int i = 0; i < 4; i++) mx[i] = fmaxf(fmaxf(dst[4 * i], dst[4 * i + 1]), fmaxf(dst[4 * i + 2], dst[4 * i + 3]));
            float mm = fmaxf(fmaxf(mx[0], mx[1]), fmaxf(mx[2], mx[3]));
            mm = fmaxf(mm, __shfl_xor_sync(0xffffffffu, mm, 1));
            mm = fmaxf(mm, __shfl_xor_sync(0xffffffffu, mm, 2));
            m = fmaxf(m, mm);
        };
        auto expo = [&](float (&x)[16]) {
            const float mc = m * c;
            float ps[4] = {0.f, 0.f, 0.f, 0.f};
#pragma unroll
            for (int j = 0; j < 16; j++) { x[j] = ex2(fmaf(x[j], c, -mc)); ps[j & 3] += x[j]; }
            return (ps[0] + ps[1]) + (ps[2] + ps[3]);
        };
        auto make_frag = [&](const float (&x)[16], float f, uint32_t (&pa)[8][4]) {
#pragma unroll
            for (int j = 0; j < 8; j++) {
                const uint32_t pk = pack_bf16(x[2 * j] * f, x[2 * j + 1] * f);
                pa[j][0] = pk & 0xFFFFu;
                pa[j][1] = pk << 16;
                pa[j][2] = pk >> 16;
                pa[j][3] = pk & 0xFFFF0000u;
#pragma unroll
                for (int r = 0; r < 4; r++) asm volatile("" : "+r"(pa[j][r]));
            }
        };
        auto scale_o = [&](float f) {
#pragma unroll
            for (int i = 0; i < 32; i++) { o[i] *= f; asm volatile("" : "+f"(o[i])); }
        };
        auto pv_issue = [&](const uint32_t (&pa)[8][4], int slot, int phase) {
            mbar_wait(full0 + 8 * slot, phase);
            const uint64_t dv = make_desc(tiles + slot * kTileBytes);
            wg_fence();
#pragma unroll
            for (int j = 0; j < 8; j++) wgmma_pv(o, pa[j], dv + j * (2048 >> 4));
            wg_commit();
        };

#pragma unroll 1
        for (int run = 0; run < kNumTiles / kRun - 1; run++) {
#pragma unroll
            for (int i = 0; i < kRun; i++) qk_step(sq[i]);
            const float alpha = ex2((mo - m) * c);
            mo = m;
            l *= alpha;
            scale_o(alpha);
#pragma unroll
            for (int i = 0; i < kRun; i++) {
                uint32_t pa[8][4];
                l += expo(sq[i]);
                make_frag(sq[i], 1.f, pa);
                pv_issue(pa, s, ph);
                wg_wait();
                if (lane == 0) mbar_arrive(empty0 + 8 * s);
                if (++s == kStages) { s = 0; ph ^= 1; }
            }
        }
#pragma unroll
        for (int i = 0; i < kRun; i++) qk_step(sq[i]);
        const float alpha = ex2((mo - m) * c);
        l *= alpha;
#pragma unroll
        for (int i = 0; i < kRun; i++) l += expo(sq[i]);
        l += __shfl_xor_sync(0xffffffffu, l, 1);
        l += __shfl_xor_sync(0xffffffffu, l, 2);
        float inv;
        asm("rcp.approx.ftz.f32 %0, %1;" : "=f"(inv) : "f"(l));
        scale_o(alpha * inv);
        uint32_t pa[kRun][8][4];
#pragma unroll
        for (int i = 0; i < kRun; i++) make_frag(sq[i], inv, pa[i]);
        uint32_t st_addr[4], ld_addr[4];
#pragma unroll
        for (int h = 0; h < 4; h++) {
            const uint32_t stage = tiles + kStages * kTileBytes + warp * 2048;
            st_addr[h] = stage + (lane & 7) * 256 + (((4 * h + (lane >> 3)) ^ (lane & 7)) << 4);
            ld_addr[h] = stage + (lane >> 4) * 256 + h * 512 + (((lane & 15) ^ (2 * h + (lane >> 4))) << 4);
        }
        {
            uint32_t x = st_addr[0] | st_addr[1] | st_addr[2] | st_addr[3] | ld_addr[0] | ld_addr[1] | ld_addr[2] | ld_addr[3];
#pragma unroll
            for (int i = 0; i < 32; i++) x |= __float_as_uint(o[i]);
#pragma unroll
            for (int i = 0; i < kRun; i++)
#pragma unroll
                for (int j = 0; j < 8; j++) x |= pa[i][j][0] | pa[i][j][1] | pa[i][j][2] | pa[i][j][3];
            s_pace[2] = x;
        }
#pragma unroll
        for (int i = 0; i < kRun; i++) {
            const int j = kChunks - kRun + i;
            pv_issue(pa[i], j % kStages, (j / kStages) & 1);
        }
        wg_wait();
#pragma unroll
        for (int i = 0; i < 32; i++) asm volatile("" : "+f"(o[i]) :: "memory");
#pragma unroll
        for (int h = 0; h < 4; h++) {
            const int e = (h >> 1) * 2, i0 = (h & 1) * 4;
            asm volatile("stmatrix.sync.aligned.m8n8.x4.shared.b16 [%0], {%1,%2,%3,%4};"
                         ::"r"(st_addr[h]),
                           "r"(pack_bf16(o[4 * i0 + e], o[4 * i0 + e + 1])), "r"(pack_bf16(o[4 * i0 + 4 + e], o[4 * i0 + 5 + e])),
                           "r"(pack_bf16(o[4 * i0 + 8 + e], o[4 * i0 + 9 + e])), "r"(pack_bf16(o[4 * i0 + 12 + e], o[4 * i0 + 13 + e])) : "memory");
        }
        __syncwarp();
#pragma unroll
        for (int h = 0; h < 4; h++) {
            uint32_t a0, a1, a2, a3;
            asm volatile("ld.shared.v4.b32 {%0,%1,%2,%3}, [%4];" : "=r"(a0), "=r"(a1), "=r"(a2), "=r"(a3)
                         : "r"(ld_addr[h]) : "memory");
            asm volatile("st.global.v4.u32 [%0], {%1,%2,%3,%4};" ::"l"(op + h * 2 * (kD / 8)), "r"(a0), "r"(a1), "r"(a2), "r"(a3) : "memory");
        }
    }
}

typedef CUresult (*EncodeTiledFn)(CUtensorMap*, CUtensorMapDataType, cuuint32_t, void*, const cuuint64_t*,
                                  const cuuint64_t*, const cuuint32_t*, const cuuint32_t*, CUtensorMapInterleave,
                                  CUtensorMapSwizzle, CUtensorMapL2promotion, CUtensorMapFloatOOBfill);

void make_map(EncodeTiledFn enc, CUtensorMap* tm, const void* base) {
    const cuuint64_t dims[2] = {64, (cuuint64_t)kB * kHkv * kSk * 2};
    const cuuint64_t strides[1] = {128};
    const cuuint32_t box[2] = {64, (cuuint32_t)kTileUnits};
    const cuuint32_t estr[2] = {1, 1};
    enc(tm, CU_TENSOR_MAP_DATA_TYPE_BFLOAT16, 2, const_cast<void*>(base), dims, strides, box, estr,
        CU_TENSOR_MAP_INTERLEAVE_NONE, CU_TENSOR_MAP_SWIZZLE_128B, CU_TENSOR_MAP_L2_PROMOTION_NONE,
        CU_TENSOR_MAP_FLOAT_OOB_FILL_NONE);
}

}

extern "C" void kernel_launch(void* const* d_in, const int* in_sizes, int n_in, void* d_out, int out_size) {
    (void)in_sizes; (void)n_in; (void)out_size;
    static EncodeTiledFn enc = nullptr;
    if (!enc) {
        cudaDriverEntryPointQueryResult qr;
        cudaGetDriverEntryPoint("cuTensorMapEncodeTiled", (void**)&enc, cudaEnableDefault, &qr);
        cudaFuncSetAttribute(gqa_decode_kernel, cudaFuncAttributeMaxDynamicSharedMemorySize, kSmemBytes);
    }
    CUtensorMap tmK, tmV;
    make_map(enc, &tmK, d_in[1]);
    make_map(enc, &tmV, d_in[2]);
    gqa_decode_kernel<<<kNumCta, kThreads, kSmemBytes>>>(tmK, tmV, (const __nv_bfloat16*)d_in[0], (__nv_bfloat16*)d_out);
}
```

```cpp
#include <cuda_runtime.h>
#include <cuda_bf16.h>
#include <cuda.h>
#include <stdint.h>

namespace {

constexpr int kB = 32, kHq = 32, kHkv = 4, kSq = 4, kSk = 2048, kD = 128;
constexpr int kRowsQ = (kHq / kHkv) * kSq;
constexpr int kNumCta = kB * kHkv;
constexpr int kTileRows = 64;
constexpr int kTileBytes = kTileRows * kD * 2;
constexpr int kTileUnits = kTileRows * 2;
constexpr int kNumTiles = kSk / kTileRows;
constexpr int kChunks = 2 * kNumTiles;
constexpr int kRun = 4;
constexpr int kStages = 10;
constexpr int kWindow = 4;
constexpr int kCredit = 704;
constexpr int kTaperFrom = 52, kTaperStep = 24;
constexpr int kMinFlight = 3, kMaxFlight = 7;
constexpr uint32_t kQDelay = 450;
constexpr int kThreads = 128 + 64;
constexpr int kSmemBytes = kStages * kTileBytes + kRowsQ * kD * 2 + 1024;

__device__ __forceinline__ uint32_t smem_u32(const void* p) { return (uint32_t)__cvta_generic_to_shared(p); }
__device__ __forceinline__ void mbar_init(uint32_t bar, uint32_t cnt) {
    asm volatile("mbarrier.init.shared::cta.b64 [%0], %1;" ::"r"(bar), "r"(cnt) : "memory");
}
__device__ __forceinline__ void mbar_expect_tx(uint32_t bar, uint32_t bytes) {
    asm volatile("mbarrier.arrive.expect_tx.shared::cta.b64 _, [%0], %1;" ::"r"(bar), "r"(bytes) : "memory");
}
__device__ __forceinline__ void mbar_arrive(uint32_t bar) {
    asm volatile("mbarrier.arrive.shared::cta.b64 _, [%0];" ::"r"(bar) : "memory");
}
__device__ __forceinline__ void mbar_wait(uint32_t bar, uint32_t parity) {
    asm volatile(
        "{\n"
        ".reg .pred p;\n"
        "WAIT_LOOP:\n"
        "mbarrier.try_wait.parity.shared::cta.b64 p, [%0], %1;\n"
        "@p bra WAIT_DONE;\n"
        "bra WAIT_LOOP;\n"
        "WAIT_DONE:\n"
        "}\n" ::"r"(bar), "r"(parity) : "memory");
}
__device__ __forceinline__ bool mbar_test(uint32_t bar, uint32_t parity) {
    uint32_t ok;
    asm volatile("{\n.reg .pred p;\nmbarrier.test_wait.parity.shared::cta.b64 p, [%1], %2;\nselp.u32 %0, 1, 0, p;\n}\n"
                 : "=r"(ok) : "r"(bar), "r"(parity) : "memory");
    return ok != 0;
}
__device__ __forceinline__ void tma_load(uint32_t dst, const CUtensorMap* tm, uint32_t bar, int unit) {
    uint64_t policy;
    asm("createpolicy.fractional.L2::evict_first.b64 %0, 1.0;" : "=l"(policy));
    asm volatile(
        "cp.async.bulk.tensor.2d.shared::cluster.global.mbarrier::complete_tx::bytes.L2::cache_hint"
        " [%0], [%1, {%3, %4}], [%2], %5;"
        ::"r"(dst), "l"(tm), "r"(bar), "r"(0), "r"(unit), "l"(policy) : "memory");
}
__device__ __forceinline__ void wg_fence() { asm volatile("wgmma.fence.sync.aligned;" ::: "memory"); }
__device__ __forceinline__ void wg_commit() { asm volatile("wgmma.commit_group.sync.aligned;" ::: "memory"); }
__device__ __forceinline__ void wg_wait() { asm volatile("wgmma.wait_group.sync.aligned 0;" ::: "memory"); }

__device__ __forceinline__ uint64_t make_desc(uint32_t addr) {
    return (uint64_t)((addr & 0x3FFFF) >> 4) | ((uint64_t)1 << 16) | ((uint64_t)(1024 >> 4) << 32) | ((uint64_t)1 << 62);
}

__device__ __forceinline__ void wgmma_qk(float (&d)[64], const uint32_t (&a)[4], uint64_t desc, int scale_d) {
    asm volatile(
        "{\n.reg .pred p;\nsetp.ne.b32 p, %69, 0;\n"
        "wgmma.mma_async.sync.aligned.m64n128k16.f32.bf16.bf16 "
        "{%0,%1,%2,%3,%4,%5,%6,%7,%8,%9,%10,%11,%12,%13,%14,%15,"
        "%16,%17,%18,%19,%20,%21,%22,%23,%24,%25,%26,%27,%28,%29,%30,%31,"
        "%32,%33,%34,%35,%36,%37,%38,%39,%40,%41,%42,%43,%44,%45,%46,%47,"
        "%48,%49,%50,%51,%52,%53,%54,%55,%56,%57,%58,%59,%60,%61,%62,%63},"
        "{%64,%65,%66,%67}, %68, p, 1, 1, 0;\n}\n"
        : "+f"(d[0]), "+f"(d[1]), "+f"(d[2]), "+f"(d[3]), "+f"(d[4]), "+f"(d[5]), "+f"(d[6]), "+f"(d[7]),
          "+f"(d[8]), "+f"(d[9]), "+f"(d[10]), "+f"(d[11]), "+f"(d[12]), "+f"(d[13]), "+f"(d[14]), "+f"(d[15]),
          "+f"(d[16]), "+f"(d[17]), "+f"(d[18]), "+f"(d[19]), "+f"(d[20]), "+f"(d[21]), "+f"(d[22]), "+f"(d[23]),
          "+f"(d[24]), "+f"(d[25]), "+f"(d[26]), "+f"(d[27]), "+f"(d[28]), "+f"(d[29]), "+f"(d[30]), "+f"(d[31]),
          "+f"(d[32]), "+f"(d[33]), "+f"(d[34]), "+f"(d[35]), "+f"(d[36]), "+f"(d[37]), "+f"(d[38]), "+f"(d[39]),
          "+f"(d[40]), "+f"(d[41]), "+f"(d[42]), "+f"(d[43]), "+f"(d[44]), "+f"(d[45]), "+f"(d[46]), "+f"(d[47]),
          "+f"(d[48]), "+f"(d[49]), "+f"(d[50]), "+f"(d[51]), "+f"(d[52]), "+f"(d[53]), "+f"(d[54]), "+f"(d[55]),
          "+f"(d[56]), "+f"(d[57]), "+f"(d[58]), "+f"(d[59]), "+f"(d[60]), "+f"(d[61]), "+f"(d[62]), "+f"(d[63])
        : "r"(a[0]), "r"(a[1]), "r"(a[2]), "r"(a[3]), "l"(desc), "r"(scale_d));
}

__device__ __forceinline__ void wgmma_pv(float (&d)[32], const uint32_t (&a)[4], uint64_t desc) {
    asm volatile(
        "wgmma.mma_async.sync.aligned.m64n64k16.f32.bf16.bf16 "
        "{%0,%1,%2,%3,%4,%5,%6,%7,%8,%9,%10,%11,%12,%13,%14,%15,"
        "%16,%17,%18,%19,%20,%21,%22,%23,%24,%25,%26,%27,%28,%29,%30,%31},"
        "{%32,%33,%34,%35}, %36, 1, 1, 1, 1;\n"
        : "+f"(d[0]), "+f"(d[1]), "+f"(d[2]), "+f"(d[3]), "+f"(d[4]), "+f"(d[5]), "+f"(d[6]), "+f"(d[7]),
          "+f"(d[8]), "+f"(d[9]), "+f"(d[10]), "+f"(d[11]), "+f"(d[12]), "+f"(d[13]), "+f"(d[14]), "+f"(d[15]),
          "+f"(d[16]), "+f"(d[17]), "+f"(d[18]), "+f"(d[19]), "+f"(d[20]), "+f"(d[21]), "+f"(d[22]), "+f"(d[23]),
          "+f"(d[24]), "+f"(d[25]), "+f"(d[26]), "+f"(d[27]), "+f"(d[28]), "+f"(d[29]), "+f"(d[30]), "+f"(d[31])
        : "r"(a[0]), "r"(a[1]), "r"(a[2]), "r"(a[3]), "l"(desc));
}

__device__ __forceinline__ uint32_t ldg_u32(const uint32_t* p) {
    uint32_t v; asm volatile("ld.global.u32 %0, [%1];" : "=r"(v) : "l"(p) : "memory"); return v;
}
__device__ __forceinline__ float ex2(float x) { float y; asm("ex2.approx.ftz.f32 %0, %1;" : "=f"(y) : "f"(x)); return y; }
__device__ __forceinline__ uint32_t pack_bf16(float lo, float hi) {
    uint32_t r; asm("cvt.rn.bf16x2.f32 %0, %1, %2;" : "=r"(r) : "f"(hi), "f"(lo)); return r;
}

__device__ unsigned int g_landed;

__device__ __forceinline__ void chunk_of(int j, bool& is_v, int& tile) {
    is_v = (j / kRun) & 1;
    tile = (j / (2 * kRun)) * kRun + j % kRun;
}

__global__ void __launch_bounds__(kThreads, 1)
gqa_decode_kernel(const __grid_constant__ CUtensorMap tmK, const __grid_constant__ CUtensorMap tmV,
                  const __nv_bfloat16* __restrict__ q, __nv_bfloat16* __restrict__ out) {
    extern __shared__ uint8_t smem_raw[];
    __shared__ __align__(8) uint64_t bars[2 * kStages];
    __shared__ volatile int s_pace[3];
    const int bh = blockIdx.x;
    const int unit0 = bh * (kSk * 2);
    const int lane = threadIdx.x & 31;

    if (threadIdx.x == 128) {
        const uint32_t tiles = (smem_u32(smem_raw) + 1023u) & ~1023u;
        const uint32_t full0 = smem_u32(&bars[0]), empty0 = full0 + 8 * kStages;
#pragma unroll
        for (int j = 0; j < kWindow; j++) mbar_init(full0 + 8 * j, 1);
        asm volatile("fence.mbarrier_init.release.cluster;" ::: "memory");
#pragma unroll
        for (int j = 0; j < kWindow; j++) {
            bool is_v; int tile;
            chunk_of(j, is_v, tile);
            mbar_expect_tx(full0 + 8 * j, kTileBytes);
            tma_load(tiles + j * kTileBytes, is_v ? &tmV : &tmK, full0 + 8 * j, unit0 + tile * kTileUnits);
        }
#pragma unroll
        for (int s = kWindow; s < kStages; s++) mbar_init(full0 + 8 * s, 1);
#pragma unroll
        for (int s = 0; s < kStages; s++) mbar_init(empty0 + 8 * s, 4);
        asm volatile("fence.mbarrier_init.release.cluster;" ::: "memory");
        s_pace[0] = 0; s_pace[1] = 0;
    }

    if (threadIdx.x >= 160) {
        asm volatile("bar.sync 2, 64;" ::: "memory");
        if (lane == 0) {
            int best = 0;
            while (!s_pace[1]) {
                unsigned v;
                asm volatile("ld.relaxed.gpu.global.u32 %0, [%1];" : "=r"(v) : "l"(&g_landed) : "memory");
                best = max(best, (int)(v & (kNumCta * kChunks - 1)));
                s_pace[0] = best;
            }
        }
    } else if (threadIdx.x >= 128) {
        const uint32_t tiles = (smem_u32(smem_raw) + 1023u) & ~1023u;
        const uint32_t full0 = smem_u32(&bars[0]), empty0 = full0 + 8 * kStages;
        __syncwarp();
        asm volatile("bar.arrive 1, 160;" ::: "memory");
        asm volatile("bar.arrive 2, 64;" ::: "memory");
        bool inflight = lane < kWindow;
        uint32_t fph = 0;
        int issued = kWindow, arrived = 0, slot = kWindow % kStages, eph = (kWindow / kStages) & 1;
        while (issued < kChunks) {
            const bool rdy = inflight && mbar_test(full0 + 8 * lane, fph);
            const int nrdy = __popc(__ballot_sync(0xffffffffu, rdy));
            arrived += nrdy;
            if (nrdy && lane == 0) asm volatile("red.relaxed.gpu.global.add.u32 [%0], %1;" ::"l"(&g_landed), "r"(nrdy) : "memory");
            const int credit = s_pace[0] + kCredit - bh;
            if (rdy) { inflight = false; fph ^= 1; }
            const uint32_t busy = __ballot_sync(0xffffffffu, inflight);
            while (issued < kChunks &&
                   (issued - arrived < kMinFlight ||
                    (issued - arrived < kMaxFlight &&
                     issued * kNumCta + max(0, issued - kTaperFrom) * kTaperStep <= credit))) {
                if (((busy >> slot) & 1) || !mbar_test(empty0 + 8 * slot, eph ^ 1)) break;
                if (lane == slot) {
                    bool is_v; int tile;
                    chunk_of(issued, is_v, tile);
                    mbar_expect_tx(full0 + 8 * slot, kTileBytes);
                    tma_load(tiles + slot * kTileBytes, is_v ? &tmV : &tmK, full0 + 8 * slot, unit0 + tile * kTileUnits);
                    inflight = true;
                }
                issued++;
                if (++slot == kStages) { slot = 0; eph ^= 1; }
            }
        }
        if (lane == 0) {
            s_pace[1] = 1;
            asm volatile("red.relaxed.gpu.global.add.u32 [%0], %1;" ::"l"(&g_landed), "r"(kChunks - arrived) : "memory");
        }
    } else {
        const int warp = __shfl_sync(0xffffffffu, threadIdx.x >> 5, 0);
        const uint32_t tiles = __shfl_sync(0xffffffffu, (smem_u32(smem_raw) + 1023u) & ~1023u, 0);
        const uint32_t full0 = __shfl_sync(0xffffffffu, smem_u32(&bars[0]), 0), empty0 = full0 + 8 * kStages;
        const int g = lane >> 2, t = lane & 3;
        {
            uint32_t t0, t1;
            asm volatile("mov.u32 %0, %clock;" : "=r"(t0) :: "memory");
            do { asm volatile("mov.u32 %0, %clock;" : "=r"(t1) :: "memory"); } while (t1 - t0 < kQDelay);
        }
        uint32_t qa[4][4];
        {
            const uint32_t* qp = reinterpret_cast<const uint32_t*>(q + (size_t)(bh * kRowsQ + warp * 8 + g) * kD) + t;
#pragma unroll
            for (int kk = 0; kk < 4; kk++) {
                qa[kk][0] = ldg_u32(qp + kk * 8);
                qa[kk][1] = ldg_u32(qp + 32 + kk * 8);
                qa[kk][2] = ldg_u32(qp + kk * 8 + 4);
                qa[kk][3] = ldg_u32(qp + 32 + kk * 8 + 4);
            }
        }
        uint4* op = reinterpret_cast<uint4*>(out + (size_t)(bh * kRowsQ + warp * 8 + (lane >> 4)) * kD) + (lane & 15);
        asm volatile("add.u64 %0, %0, 0;" : "+l"(op));
        float o[32];
#pragma unroll
        for (int i = 0; i < 32; i++) o[i] = 0.f;
        float m = -INFINITY;
        float mo = -INFINITY;
        float l = 0.f;
        float sq[kRun][16];
        const float c = 0.08838834764831845f * 1.4426950408889634f;
        asm volatile("bar.sync 1, 160;" ::: "memory");

        int s = 0, ph = 0;

        auto qk_step = [&](float (&dst)[16]) {
            float sc[64];
            mbar_wait(full0 + 8 * s, ph);
            const uint64_t dk = make_desc(tiles + s * kTileBytes);
            wg_fence();
#pragma unroll
            for (int kk = 0; kk < 4; kk++) wgmma_qk(sc, qa[kk], dk + kk * 2, kk);
            wg_commit();
            wg_wait();
            if (lane == 0) mbar_arrive(empty0 + 8 * s);
            if (++s == kStages) { s = 0; ph ^= 1; }
#pragma unroll
            for (int i = 0; i < 64; i++) asm volatile("" : "+f"(sc[i]) :: "memory");
#pragma unroll
            for (int i = 0; i < 16; i++) dst[i] = sc[4 * i] + sc[4 * i + 3];
            float mx[4];
#pragma unroll
            for (int i = 0; i < 4; i++) mx[i] = fmaxf(fmaxf(dst[4 * i], dst[4 * i + 1]), fmaxf(dst[4 * i + 2], dst[4 * i + 3]));
            float mm = fmaxf(fmaxf(mx[0], mx[1]), fmaxf(mx[2], mx[3]));
            mm = fmaxf(mm, __shfl_xor_sync(0xffffffffu, mm, 1));
            mm = fmaxf(mm, __shfl_xor_sync(0xffffffffu, mm, 2));
            m = fmaxf(m, mm);
        };
        auto expo = [&](float (&x)[16]) {
            const float mc = m * c;
            float ps[4] = {0.f, 0.f, 0.f, 0.f};
#pragma unroll
            for (int j = 0; j < 16; j++) { x[j] = ex2(fmaf(x[j], c, -mc)); ps[j & 3] += x[j]; }
            return (ps[0] + ps[1]) + (ps[2] + ps[3]);
        };
        auto make_frag = [&](const float (&x)[16], float f, uint32_t (&pa)[8][4]) {
#pragma unroll
            for (int j = 0; j < 8; j++) {
                const uint32_t pk = pack_bf16(x[2 * j] * f, x[2 * j + 1] * f);
                pa[j][0] = pk & 0xFFFFu;
                pa[j][1] = pk << 16;
                pa[j][2] = pk >> 16;
                pa[j][3] = pk & 0xFFFF0000u;
#pragma unroll
                for (int r = 0; r < 4; r++) asm volatile("" : "+r"(pa[j][r]));
            }
        };
        auto scale_o = [&](float f) {
#pragma unroll
            for (int i = 0; i < 32; i++) { o[i] *= f; asm volatile("" : "+f"(o[i])); }
        };
        auto pv_issue = [&](const uint32_t (&pa)[8][4], int slot, int phase) {
            mbar_wait(full0 + 8 * slot, phase);
            const uint64_t dv = make_desc(tiles + slot * kTileBytes);
            wg_fence();
#pragma unroll
            for (int j = 0; j < 8; j++) wgmma_pv(o, pa[j], dv + j * (2048 >> 4));
            wg_commit();
        };

#pragma unroll 1
        for (int run = 0; run < kNumTiles / kRun - 1; run++) {
#pragma unroll
            for (int i = 0; i < kRun; i++) qk_step(sq[i]);
            const float alpha = ex2((mo - m) * c);
            mo = m;
            l *= alpha;
            scale_o(alpha);
#pragma unroll
            for (int i = 0; i < kRun; i++) {
                uint32_t pa[8][4];
                l += expo(sq[i]);
                make_frag(sq[i], 1.f, pa);
                pv_issue(pa, s, ph);
                wg_wait();
                if (lane == 0) mbar_arrive(empty0 + 8 * s);
                if (++s == kStages) { s = 0; ph ^= 1; }
            }
        }
#pragma unroll
        for (int i = 0; i < kRun; i++) qk_step(sq[i]);
        const float alpha = ex2((mo - m) * c);
        l *= alpha;
#pragma unroll
        for (int i = 0; i < kRun; i++) l += expo(sq[i]);
        l += __shfl_xor_sync(0xffffffffu, l, 1);
        l += __shfl_xor_sync(0xffffffffu, l, 2);
        float inv;
        asm("rcp.approx.ftz.f32 %0, %1;" : "=f"(inv) : "f"(l));
        scale_o(alpha * inv);
        uint32_t pa[kRun][8][4];
#pragma unroll
        for (int i = 0; i < kRun; i++) make_frag(sq[i], inv, pa[i]);
        uint32_t st_addr[4], ld_addr[4];
#pragma unroll
        for (int h = 0; h < 4; h++) {
            const uint32_t stage = tiles + kStages * kTileBytes + warp * 2048;
            st_addr[h] = stage + (lane & 7) * 256 + (((4 * h + (lane >> 3)) ^ (lane & 7)) << 4);
            ld_addr[h] = stage + (lane >> 4) * 256 + h * 512 + (((lane & 15) ^ (2 * h + (lane >> 4))) << 4);
        }
        {
            uint32_t x = st_addr[0] | st_addr[1] | st_addr[2] | st_addr[3] | ld_addr[0] | ld_addr[1] | ld_addr[2] | ld_addr[3];
#pragma unroll
            for (int i = 0; i < 32; i++) x |= __float_as_uint(o[i]);
#pragma unroll
            for (int i = 0; i < kRun; i++)
#pragma unroll
                for (int j = 0; j < 8; j++) x |= pa[i][j][0] | pa[i][j][1] | pa[i][j][2] | pa[i][j][3];
            s_pace[2] = x;
        }
#pragma unroll
        for (int i = 0; i < kRun; i++) {
            const int j = kChunks - kRun + i;
            pv_issue(pa[i], j % kStages, (j / kStages) & 1);
        }
        wg_wait();
#pragma unroll
        for (int i = 0; i < 32; i++) asm volatile("" : "+f"(o[i]) :: "memory");
#pragma unroll
        for (int h = 0; h < 4; h++) {
            const int e = (h >> 1) * 2, i0 = (h & 1) * 4;
            asm volatile("stmatrix.sync.aligned.m8n8.x4.shared.b16 [%0], {%1,%2,%3,%4};"
                         ::"r"(st_addr[h]),
                           "r"(pack_bf16(o[4 * i0 + e], o[4 * i0 + e + 1])), "r"(pack_bf16(o[4 * i0 + 4 + e], o[4 * i0 + 5 + e])),
                           "r"(pack_bf16(o[4 * i0 + 8 + e], o[4 * i0 + 9 + e])), "r"(pack_bf16(o[4 * i0 + 12 + e], o[4 * i0 + 13 + e])) : "memory");
        }
        __syncwarp();
#pragma unroll
        for (int h = 0; h < 4; h++) {
            uint32_t a0, a1, a2, a3;
            asm volatile("ld.shared.v4.b32 {%0,%1,%2,%3}, [%4];" : "=r"(a0), "=r"(a1), "=r"(a2), "=r"(a3)
                         : "r"(ld_addr[h]) : "memory");
            asm volatile("st.global.v4.u32 [%0], {%1,%2,%3,%4};" ::"l"(op + h * 2 * (kD / 8)), "r"(a0), "r"(a1), "r"(a2), "r"(a3) : "memory");
        }
    }
}

typedef CUresult (*EncodeTiledFn)(CUtensorMap*, CUtensorMapDataType, cuuint32_t, void*, const cuuint64_t*,
                                  const cuuint64_t*, const cuuint32_t*, const cuuint32_t*, CUtensorMapInterleave,
                                  CUtensorMapSwizzle, CUtensorMapL2promotion, CUtensorMapFloatOOBfill);

void make_map(EncodeTiledFn enc, CUtensorMap* tm, const void* base) {
    const cuuint64_t dims[2] = {64, (cuuint64_t)kB * kHkv * kSk * 2};
    const cuuint64_t strides[1] = {128};
    const cuuint32_t box[2] = {64, (cuuint32_t)kTileUnits};
    const cuuint32_t estr[2] = {1, 1};
    enc(tm, CU_TENSOR_MAP_DATA_TYPE_BFLOAT16, 2, const_cast<void*>(base), dims, strides, box, estr,
        CU_TENSOR_MAP_INTERLEAVE_NONE, CU_TENSOR_MAP_SWIZZLE_128B, CU_TENSOR_MAP_L2_PROMOTION_NONE,
        CU_TENSOR_MAP_FLOAT_OOB_FILL_NONE);
}

}

extern "C" void kernel_launch(void* const* d_in, const int* in_sizes, int n_in, void* d_out, int out_size) {
    (void)in_sizes; (void)n_in; (void)out_size;
    cudaLaunchAttribute attr;
    attr.id = cudaLaunchAttributeClusterDimension;
    attr.val.clusterDim.x = 2; attr.val.clusterDim.y = 1; attr.val.clusterDim.z = 1;
    cudaLaunchConfig_t cfg = {};
    cfg.gridDim = dim3(kNumCta); cfg.blockDim = dim3(kThreads); cfg.dynamicSmemBytes = kSmemBytes;
    cfg.stream = cudaStreamPerThread; cfg.attrs = &attr; cfg.numAttrs = 1;

    static EncodeTiledFn enc = nullptr;
    static unsigned cluster = 1;
    if (!enc) {
        cudaDriverEntryPointQueryResult qr;
        cudaGetDriverEntryPoint("cuTensorMapEncodeTiled", (void**)&enc, cudaEnableDefault, &qr);
        cudaFuncSetAttribute(gqa_decode_kernel, cudaFuncAttributeMaxDynamicSharedMemorySize, kSmemBytes);
        int n = 0;
        if (cudaOccupancyMaxActiveClusters(&n, gqa_decode_kernel, &cfg) == cudaSuccess && 2 * n >= kNumCta) cluster = 2;
        (void)cudaGetLastError();
    }
    attr.val.clusterDim.x = cluster;
    CUtensorMap tmK, tmV;
    make_map(enc, &tmK, d_in[1]);
    make_map(enc, &tmV, d_in[2]);
    cudaLaunchKernelEx(&cfg, gqa_decode_kernel, tmK, tmV, (const __nv_bfloat16*)d_in[0], (__nv_bfloat16*)d_out);
}
```

```cpp
#include <cuda_runtime.h>
#include <cuda_bf16.h>
#include <cuda.h>
#include <stdint.h>

namespace {

constexpr int kB = 32, kHq = 32, kHkv = 4, kSq = 4, kSk = 2048, kD = 128;
constexpr int kRowsQ = (kHq / kHkv) * kSq;
constexpr int kNumCta = kB * kHkv;
constexpr int kTileRows = 64;
constexpr int kTileBytes = kTileRows * kD * 2;
constexpr int kTileUnits = kTileRows * 2;
constexpr int kNumTiles = kSk / kTileRows;
constexpr int kChunks = 2 * kNumTiles;
constexpr int kRun = 4;
constexpr int kStages = 10;
constexpr int kWindow = 4;
constexpr int kCredit = 704;
constexpr int kTaperFrom = 52, kTaperStep = 24;
constexpr int kMinFlight = 3, kMaxFlight = 7;
constexpr uint32_t kQDelay = 450;
constexpr int kThreads = 128 + 64;
constexpr int kSmemBytes = kStages * kTileBytes + kRowsQ * kD * 2 + 1024;

__device__ __forceinline__ uint32_t smem_u32(const void* p) { return (uint32_t)__cvta_generic_to_shared(p); }
__device__ __forceinline__ void mbar_init(uint32_t bar, uint32_t cnt) {
    asm volatile("mbarrier.init.shared::cta.b64 [%0], %1;" ::"r"(bar), "r"(cnt) : "memory");
}
__device__ __forceinline__ void mbar_expect_tx(uint32_t bar, uint32_t bytes) {
    asm volatile("mbarrier.arrive.expect_tx.shared::cta.b64 _, [%0], %1;" ::"r"(bar), "r"(bytes) : "memory");
}
__device__ __forceinline__ void mbar_arrive(uint32_t bar) {
    asm volatile("mbarrier.arrive.shared::cta.b64 _, [%0];" ::"r"(bar) : "memory");
}
__device__ __forceinline__ void mbar_wait(uint32_t bar, uint32_t parity) {
    asm volatile(
        "{\n"
        ".reg .pred p;\n"
        "WAIT_LOOP:\n"
        "mbarrier.try_wait.parity.shared::cta.b64 p, [%0], %1;\n"
        "@p bra WAIT_DONE;\n"
        "bra WAIT_LOOP;\n"
        "WAIT_DONE:\n"
        "}\n" ::"r"(bar), "r"(parity) : "memory");
}
__device__ __forceinline__ bool mbar_test(uint32_t bar, uint32_t parity) {
    uint32_t ok;
    asm volatile("{\n.reg .pred p;\nmbarrier.test_wait.parity.shared::cta.b64 p, [%1], %2;\nselp.u32 %0, 1, 0, p;\n}\n"
                 : "=r"(ok) : "r"(bar), "r"(parity) : "memory");
    return ok != 0;
}
__device__ __forceinline__ void tma_load(uint32_t dst, const CUtensorMap* tm, uint32_t bar, int unit) {
    uint64_t policy;
    asm("createpolicy.fractional.L2::evict_first.b64 %0, 1.0;" : "=l"(policy));
    asm volatile(
        "cp.async.bulk.tensor.2d.shared::cluster.global.mbarrier::complete_tx::bytes.L2::cache_hint"
        " [%0], [%1, {%3, %4}], [%2], %5;"
        ::"r"(dst), "l"(tm), "r"(bar), "r"(0), "r"(unit), "l"(policy) : "memory");
}
__device__ __forceinline__ void wg_fence() { asm volatile("wgmma.fence.sync.aligned;" ::: "memory"); }
__device__ __forceinline__ void wg_commit() { asm volatile("wgmma.commit_group.sync.aligned;" ::: "memory"); }
__device__ __forceinline__ void wg_wait() { asm volatile("wgmma.wait_group.sync.aligned 0;" ::: "memory"); }

__device__ __forceinline__ uint64_t make_desc(uint32_t addr) {
    return (uint64_t)((addr & 0x3FFFF) >> 4) | ((uint64_t)1 << 16) | ((uint64_t)(1024 >> 4) << 32) | ((uint64_t)1 << 62);
}

__device__ __forceinline__ void wgmma_qk(float (&d)[64], const uint32_t (&a)[4], uint64_t desc, int scale_d) {
    asm volatile(
        "{\n.reg .pred p;\nsetp.ne.b32 p, %69, 0;\n"
        "wgmma.mma_async.sync.aligned.m64n128k16.f32.bf16.bf16 "
        "{%0,%1,%2,%3,%4,%5,%6,%7,%8,%9,%10,%11,%12,%13,%14,%15,"
        "%16,%17,%18,%19,%20,%21,%22,%23,%24,%25,%26,%27,%28,%29,%30,%31,"
        "%32,%33,%34,%35,%36,%37,%38,%39,%40,%41,%42,%43,%44,%45,%46,%47,"
        "%48,%49,%50,%51,%52,%53,%54,%55,%56,%57,%58,%59,%60,%61,%62,%63},"
        "{%64,%65,%66,%67}, %68, p, 1, 1, 0;\n}\n"
        : "+f"(d[0]), "+f"(d[1]), "+f"(d[2]), "+f"(d[3]), "+f"(d[4]), "+f"(d[5]), "+f"(d[6]), "+f"(d[7]),
          "+f"(d[8]), "+f"(d[9]), "+f"(d[10]), "+f"(d[11]), "+f"(d[12]), "+f"(d[13]), "+f"(d[14]), "+f"(d[15]),
          "+f"(d[16]), "+f"(d[17]), "+f"(d[18]), "+f"(d[19]), "+f"(d[20]), "+f"(d[21]), "+f"(d[22]), "+f"(d[23]),
          "+f"(d[24]), "+f"(d[25]), "+f"(d[26]), "+f"(d[27]), "+f"(d[28]), "+f"(d[29]), "+f"(d[30]), "+f"(d[31]),
          "+f"(d[32]), "+f"(d[33]), "+f"(d[34]), "+f"(d[35]), "+f"(d[36]), "+f"(d[37]), "+f"(d[38]), "+f"(d[39]),
          "+f"(d[40]), "+f"(d[41]), "+f"(d[42]), "+f"(d[43]), "+f"(d[44]), "+f"(d[45]), "+f"(d[46]), "+f"(d[47]),
          "+f"(d[48]), "+f"(d[49]), "+f"(d[50]), "+f"(d[51]), "+f"(d[52]), "+f"(d[53]), "+f"(d[54]), "+f"(d[55]),
          "+f"(d[56]), "+f"(d[57]), "+f"(d[58]), "+f"(d[59]), "+f"(d[60]), "+f"(d[61]), "+f"(d[62]), "+f"(d[63])
        : "r"(a[0]), "r"(a[1]), "r"(a[2]), "r"(a[3]), "l"(desc), "r"(scale_d));
}

__device__ __forceinline__ void wgmma_pv(float (&d)[32], const uint32_t (&a)[4], uint64_t desc) {
    asm volatile(
        "wgmma.mma_async.sync.aligned.m64n64k16.f32.bf16.bf16 "
        "{%0,%1,%2,%3,%4,%5,%6,%7,%8,%9,%10,%11,%12,%13,%14,%15,"
        "%16,%17,%18,%19,%20,%21,%22,%23,%24,%25,%26,%27,%28,%29,%30,%31},"
        "{%32,%33,%34,%35}, %36, 1, 1, 1, 1;\n"
        : "+f"(d[0]), "+f"(d[1]), "+f"(d[2]), "+f"(d[3]), "+f"(d[4]), "+f"(d[5]), "+f"(d[6]), "+f"(d[7]),
          "+f"(d[8]), "+f"(d[9]), "+f"(d[10]), "+f"(d[11]), "+f"(d[12]), "+f"(d[13]), "+f"(d[14]), "+f"(d[15]),
          "+f"(d[16]), "+f"(d[17]), "+f"(d[18]), "+f"(d[19]), "+f"(d[20]), "+f"(d[21]), "+f"(d[22]), "+f"(d[23]),
          "+f"(d[24]), "+f"(d[25]), "+f"(d[26]), "+f"(d[27]), "+f"(d[28]), "+f"(d[29]), "+f"(d[30]), "+f"(d[31])
        : "r"(a[0]), "r"(a[1]), "r"(a[2]), "r"(a[3]), "l"(desc));
}

__device__ __forceinline__ uint32_t ldg_u32(const uint32_t* p) {
    uint32_t v; asm volatile("ld.global.u32 %0, [%1];" : "=r"(v) : "l"(p) : "memory"); return v;
}
__device__ __forceinline__ float ex2(float x) { float y; asm("ex2.approx.ftz.f32 %0, %1;" : "=f"(y) : "f"(x)); return y; }
__device__ __forceinline__ uint32_t pack_bf16(float lo, float hi) {
    uint32_t r; asm("cvt.rn.bf16x2.f32 %0, %1, %2;" : "=r"(r) : "f"(hi), "f"(lo)); return r;
}

__device__ unsigned int g_landed;

__device__ __forceinline__ void chunk_of(int j, bool& is_v, int& tile) {
    is_v = (j / kRun) & 1;
    tile = (j / (2 * kRun)) * kRun + j % kRun;
}

__global__ void __launch_bounds__(kThreads, 1)
gqa_decode_kernel(const __grid_constant__ CUtensorMap tmK, const __grid_constant__ CUtensorMap tmV,
                  const __nv_bfloat16* __restrict__ q, __nv_bfloat16* __restrict__ out) {
    extern __shared__ uint8_t smem_raw[];
    __shared__ __align__(8) uint64_t bars[2 * kStages];
    __shared__ volatile int s_pace[3];
    const int bh = blockIdx.x;
    const int unit0 = bh * (kSk * 2);
    const int lane = threadIdx.x & 31;

    if (threadIdx.x == 128) {
        const uint32_t tiles = (smem_u32(smem_raw) + 1023u) & ~1023u;
        const uint32_t full0 = smem_u32(&bars[0]), empty0 = full0 + 8 * kStages;
#pragma unroll
        for (int j = 0; j < kWindow; j++) mbar_init(full0 + 8 * j, 1);
        asm volatile("fence.mbarrier_init.release.cluster;" ::: "memory");
#pragma unroll
        for (int j = 0; j < kWindow; j++) {
            bool is_v; int tile;
            chunk_of(j, is_v, tile);
            mbar_expect_tx(full0 + 8 * j, kTileBytes);
            tma_load(tiles + j * kTileBytes, is_v ? &tmV : &tmK, full0 + 8 * j, unit0 + tile * kTileUnits);
        }
#pragma unroll
        for (int s = kWindow; s < kStages; s++) mbar_init(full0 + 8 * s, 1);
#pragma unroll
        for (int s = 0; s < kStages; s++) mbar_init(empty0 + 8 * s, 4);
        asm volatile("fence.mbarrier_init.release.cluster;" ::: "memory");
        s_pace[0] = 0; s_pace[1] = 0;
    }

    if (threadIdx.x >= 160) {
        asm volatile("bar.sync 2, 64;" ::: "memory");
        if (lane == 0) {
            int best = 0;
            while (!s_pace[1]) {
                unsigned v;
                asm volatile("ld.relaxed.gpu.global.u32 %0, [%1];" : "=r"(v) : "l"(&g_landed) : "memory");
                best = max(best, (int)v);
                s_pace[0] = best;
            }
        }
    } else if (threadIdx.x >= 128) {
        const uint32_t tiles = (smem_u32(smem_raw) + 1023u) & ~1023u;
        const uint32_t full0 = smem_u32(&bars[0]), empty0 = full0 + 8 * kStages;
        __syncwarp();
        asm volatile("bar.arrive 1, 160;" ::: "memory");
        asm volatile("bar.arrive 2, 64;" ::: "memory");
        bool inflight = lane < kWindow;
        uint32_t fph = 0;
        int issued = kWindow, arrived = 0, slot = kWindow % kStages, eph = (kWindow / kStages) & 1;
        while (issued < kChunks) {
            const bool rdy = inflight && mbar_test(full0 + 8 * lane, fph);
            const int nrdy = __popc(__ballot_sync(0xffffffffu, rdy));
            arrived += nrdy;
            if (nrdy && lane == 0) asm volatile("red.relaxed.gpu.global.add.u32 [%0], %1;" ::"l"(&g_landed), "r"(nrdy) : "memory");
            const int credit = __shfl_sync(0xffffffffu, s_pace[0], 0) + kCredit - bh;
            if (rdy) { inflight = false; fph ^= 1; }
            const uint32_t busy = __ballot_sync(0xffffffffu, inflight);
            while (issued < kChunks &&
                   (issued - arrived < kMinFlight ||
                    (issued - arrived < kMaxFlight &&
                     issued * kNumCta + max(0, issued - kTaperFrom) * kTaperStep <= credit))) {
                if (((busy >> slot) & 1) || !__all_sync(0xffffffffu, mbar_test(empty0 + 8 * slot, eph ^ 1))) break;
                if (lane == slot) {
                    bool is_v; int tile;
                    chunk_of(issued, is_v, tile);
                    mbar_expect_tx(full0 + 8 * slot, kTileBytes);
                    tma_load(tiles + slot * kTileBytes, is_v ? &tmV : &tmK, full0 + 8 * slot, unit0 + tile * kTileUnits);
                    inflight = true;
                }
                issued++;
                if (++slot == kStages) { slot = 0; eph ^= 1; }
            }
        }
        if (lane == 0) {
            s_pace[1] = 1;
            const unsigned rest = kChunks - arrived;
            if (atomicAdd(&g_landed, rest) + rest == kNumCta * kChunks) atomicExch(&g_landed, 0u);
        }
    } else {
        const int warp = __shfl_sync(0xffffffffu, threadIdx.x >> 5, 0);
        const uint32_t tiles = __shfl_sync(0xffffffffu, (smem_u32(smem_raw) + 1023u) & ~1023u, 0);
        const uint32_t full0 = __shfl_sync(0xffffffffu, smem_u32(&bars[0]), 0), empty0 = full0 + 8 * kStages;
        const int g = lane >> 2, t = lane & 3;
        {
            uint32_t t0, t1;
            asm volatile("mov.u32 %0, %clock;" : "=r"(t0) :: "memory");
            do { asm volatile("mov.u32 %0, %clock;" : "=r"(t1) :: "memory"); } while (t1 - t0 < kQDelay);
        }
        uint32_t qa[4][4];
        {
            const uint32_t* qp = reinterpret_cast<const uint32_t*>(q + (size_t)(bh * kRowsQ + warp * 8 + g) * kD) + t;
#pragma unroll
            for (int kk = 0; kk < 4; kk++) {
                qa[kk][0] = ldg_u32(qp + kk * 8);
                qa[kk][1] = ldg_u32(qp + 32 + kk * 8);
                qa[kk][2] = ldg_u32(qp + kk * 8 + 4);
                qa[kk][3] = ldg_u32(qp + 32 + kk * 8 + 4);
            }
        }
        uint4* op = reinterpret_cast<uint4*>(out + (size_t)(bh * kRowsQ + warp * 8 + (lane >> 4)) * kD) + (lane & 15);
        asm volatile("add.u64 %0, %0, 0;" : "+l"(op));
        float o[32];
#pragma unroll
        for (int i = 0; i < 32; i++) o[i] = 0.f;
        float m = -INFINITY;
        float mo = -INFINITY;
        float l = 0.f;
        float sq[kRun][16];
        const float c = 0.08838834764831845f * 1.4426950408889634f;
        asm volatile("bar.sync 1, 160;" ::: "memory");

        int s = 0, ph = 0;

        auto qk_step = [&](float (&dst)[16]) {
            float sc[64];
            mbar_wait(full0 + 8 * s, ph);
            const uint64_t dk = make_desc(tiles + s * kTileBytes);
            wg_fence();
#pragma unroll
            for (int kk = 0; kk < 4; kk++) wgmma_qk(sc, qa[kk], dk + kk * 2, kk);
            wg_commit();
            wg_wait();
            if (lane == 0) mbar_arrive(empty0 + 8 * s);
            if (++s == kStages) { s = 0; ph ^= 1; }
#pragma unroll
            for (int i = 0; i < 64; i++) asm volatile("" : "+f"(sc[i]) :: "memory");
#pragma unroll
            for (int i = 0; i < 16; i++) dst[i] = sc[4 * i] + sc[4 * i + 3];
            float mx[4];
#pragma unroll
            for (int i = 0; i < 4; i++) mx[i] = fmaxf(fmaxf(dst[4 * i], dst[4 * i + 1]), fmaxf(dst[4 * i + 2], dst[4 * i + 3]));
            float mm = fmaxf(fmaxf(mx[0], mx[1]), fmaxf(mx[2], mx[3]));
            mm = fmaxf(mm, __shfl_xor_sync(0xffffffffu, mm, 1));
            mm = fmaxf(mm, __shfl_xor_sync(0xffffffffu, mm, 2));
            m = fmaxf(m, mm);
        };
        auto expo = [&](float (&x)[16]) {
            const float mc = m * c;
            float ps[4] = {0.f, 0.f, 0.f, 0.f};
#pragma unroll
            for (int j = 0; j < 16; j++) { x[j] = ex2(fmaf(x[j], c, -mc)); ps[j & 3] += x[j]; }
            return (ps[0] + ps[1]) + (ps[2] + ps[3]);
        };
        auto make_frag = [&](const float (&x)[16], float f, uint32_t (&pa)[8][4]) {
#pragma unroll
            for (int j = 0; j < 8; j++) {
                const uint32_t pk = pack_bf16(x[2 * j] * f, x[2 * j + 1] * f);
                pa[j][0] = pk & 0xFFFFu;
                pa[j][1] = pk << 16;
                pa[j][2] = pk >> 16;
                pa[j][3] = pk & 0xFFFF0000u;
#pragma unroll
                for (int r = 0; r < 4; r++) asm volatile("" : "+r"(pa[j][r]));
            }
        };
        auto scale_o = [&](float f) {
#pragma unroll
            for (int i = 0; i < 32; i++) { o[i] *= f; asm volatile("" : "+f"(o[i])); }
        };
        auto pv_issue = [&](const uint32_t (&pa)[8][4], int slot, int phase) {
            mbar_wait(full0 + 8 * slot, phase);
            const uint64_t dv = make_desc(tiles + slot * kTileBytes);
            wg_fence();
#pragma unroll
            for (int j = 0; j < 8; j++) wgmma_pv(o, pa[j], dv + j * (2048 >> 4));
            wg_commit();
        };

#pragma unroll 1
        for (int run = 0; run < kNumTiles / kRun - 1; run++) {
#pragma unroll
            for (int i = 0; i < kRun; i++) qk_step(sq[i]);
            const float alpha = ex2((mo - m) * c);
            mo = m;
            l *= alpha;
            scale_o(alpha);
#pragma unroll
            for (int i = 0; i < kRun; i++) {
                uint32_t pa[8][4];
                l += expo(sq[i]);
                make_frag(sq[i], 1.f, pa);
                pv_issue(pa, s, ph);
                wg_wait();
                if (lane == 0) mbar_arrive(empty0 + 8 * s);
                if (++s == kStages) { s = 0; ph ^= 1; }
            }
        }
#pragma unroll
        for (int i = 0; i < kRun; i++) qk_step(sq[i]);
        const float alpha = ex2((mo - m) * c);
        l *= alpha;
#pragma unroll
        for (int i = 0; i < kRun; i++) l += expo(sq[i]);
        l += __shfl_xor_sync(0xffffffffu, l, 1);
        l += __shfl_xor_sync(0xffffffffu, l, 2);
        float inv;
        asm("rcp.approx.ftz.f32 %0, %1;" : "=f"(inv) : "f"(l));
        scale_o(alpha * inv);
        uint32_t pa[kRun][8][4];
#pragma unroll
        for (int i = 0; i < kRun; i++) make_frag(sq[i], inv, pa[i]);
        uint32_t st_addr[4], ld_addr[4];
#pragma unroll
        for (int h = 0; h < 4; h++) {
            const uint32_t stage = tiles + kStages * kTileBytes + warp * 2048;
            st_addr[h] = stage + (lane & 7) * 256 + (((4 * h + (lane >> 3)) ^ (lane & 7)) << 4);
            ld_addr[h] = stage + (lane >> 4) * 256 + h * 512 + (((lane & 15) ^ (2 * h + (lane >> 4))) << 4);
        }
        {
            uint32_t x = st_addr[0] | st_addr[1] | st_addr[2] | st_addr[3] | ld_addr[0] | ld_addr[1] | ld_addr[2] | ld_addr[3];
#pragma unroll
            for (int i = 0; i < 32; i++) x |= __float_as_uint(o[i]);
#pragma unroll
            for (int i = 0; i < kRun; i++)
#pragma unroll
                for (int j = 0; j < 8; j++) x |= pa[i][j][0] | pa[i][j][1] | pa[i][j][2] | pa[i][j][3];
            s_pace[2] = x;
        }
#pragma unroll
        for (int i = 0; i < kRun; i++) {
            const int j = kChunks - kRun + i;
            pv_issue(pa[i], j % kStages, (j / kStages) & 1);
        }
        wg_wait();
#pragma unroll
        for (int i = 0; i < 32; i++) asm volatile("" : "+f"(o[i]) :: "memory");
#pragma unroll
        for (int h = 0; h < 4; h++) {
            const int e = (h >> 1) * 2, i0 = (h & 1) * 4;
            asm volatile("stmatrix.sync.aligned.m8n8.x4.shared.b16 [%0], {%1,%2,%3,%4};"
                         ::"r"(st_addr[h]),
                           "r"(pack_bf16(o[4 * i0 + e], o[4 * i0 + e + 1])), "r"(pack_bf16(o[4 * i0 + 4 + e], o[4 * i0 + 5 + e])),
                           "r"(pack_bf16(o[4 * i0 + 8 + e], o[4 * i0 + 9 + e])), "r"(pack_bf16(o[4 * i0 + 12 + e], o[4 * i0 + 13 + e])) : "memory");
        }
        __syncwarp();
#pragma unroll
        for (int h = 0; h < 4; h++) {
            uint32_t a0, a1, a2, a3;
            asm volatile("ld.shared.v4.b32 {%0,%1,%2,%3}, [%4];" : "=r"(a0), "=r"(a1), "=r"(a2), "=r"(a3)
                         : "r"(ld_addr[h]) : "memory");
            asm volatile("st.global.v4.u32 [%0], {%1,%2,%3,%4};" ::"l"(op + h * 2 * (kD / 8)), "r"(a0), "r"(a1), "r"(a2), "r"(a3) : "memory");
        }
    }
}

typedef CUresult (*EncodeTiledFn)(CUtensorMap*, CUtensorMapDataType, cuuint32_t, void*, const cuuint64_t*,
                                  const cuuint64_t*, const cuuint32_t*, const cuuint32_t*, CUtensorMapInterleave,
                                  CUtensorMapSwizzle, CUtensorMapL2promotion, CUtensorMapFloatOOBfill);

void make_map(EncodeTiledFn enc, CUtensorMap* tm, const void* base) {
    const cuuint64_t dims[2] = {64, (cuuint64_t)kB * kHkv * kSk * 2};
    const cuuint64_t strides[1] = {128};
    const cuuint32_t box[2] = {64, (cuuint32_t)kTileUnits};
    const cuuint32_t estr[2] = {1, 1};
    enc(tm, CU_TENSOR_MAP_DATA_TYPE_BFLOAT16, 2, const_cast<void*>(base), dims, strides, box, estr,
        CU_TENSOR_MAP_INTERLEAVE_NONE, CU_TENSOR_MAP_SWIZZLE_128B, CU_TENSOR_MAP_L2_PROMOTION_NONE,
        CU_TENSOR_MAP_FLOAT_OOB_FILL_NONE);
}

}

extern "C" void kernel_launch(void* const* d_in, const int* in_sizes, int n_in, void* d_out, int out_size) {
    (void)in_sizes; (void)n_in; (void)out_size;
    cudaLaunchAttribute attr;
    attr.id = cudaLaunchAttributeClusterDimension;
    attr.val.clusterDim.x = 2; attr.val.clusterDim.y = 1; attr.val.clusterDim.z = 1;
    cudaLaunchConfig_t cfg = {};
    cfg.gridDim = dim3(kNumCta); cfg.blockDim = dim3(kThreads); cfg.dynamicSmemBytes = kSmemBytes;
    cfg.stream = cudaStreamPerThread; cfg.attrs = &attr; cfg.numAttrs = 1;

    static EncodeTiledFn enc = nullptr;
    static unsigned cluster = 1;
    if (!enc) {
        cudaDriverEntryPointQueryResult qr;
        cudaGetDriverEntryPoint("cuTensorMapEncodeTiled", (void**)&enc, cudaEnableDefault, &qr);
        cudaFuncSetAttribute(gqa_decode_kernel, cudaFuncAttributeMaxDynamicSharedMemorySize, kSmemBytes);
        int n = 0;
        if (cudaOccupancyMaxActiveClusters(&n, gqa_decode_kernel, &cfg) == cudaSuccess && 2 * n >= kNumCta) cluster = 2;
        (void)cudaGetLastError();
    }
    attr.val.clusterDim.x = cluster;
    CUtensorMap tmK, tmV;
    make_map(enc, &tmK, d_in[1]);
    make_map(enc, &tmV, d_in[2]);
    cudaLaunchKernelEx(&cfg, gqa_decode_kernel, tmK, tmV, (const __nv_bfloat16*)d_in[0], (__nv_bfloat16*)d_out);
}
```

```cpp
#include <cuda_runtime.h>
#include <cuda_bf16.h>
#include <cuda.h>
#include <stdint.h>

namespace {

constexpr int kB = 32, kHq = 32, kHkv = 4, kSq = 4, kSk = 2048, kD = 128;
constexpr int kRowsQ = (kHq / kHkv) * kSq;
constexpr int kNumCta = kB * kHkv;
constexpr int kTileRows = 64;
constexpr int kTileBytes = kTileRows * kD * 2;
constexpr int kTileUnits = kTileRows * 2;
constexpr int kNumTiles = kSk / kTileRows;
constexpr int kChunks = 2 * kNumTiles;
constexpr int kRun = 4;
constexpr int kStages = 2 * kRun;
constexpr int kWindow = 4;
constexpr int kCredit = 704;
constexpr int kTaperFrom = 52, kTaperStep = 24;
constexpr int kMinFlight = 3, kMaxFlight = 6;
constexpr uint32_t kQDelay = 450;
constexpr int kThreads = 128 + 64;
constexpr int kSmemBytes = kStages * kTileBytes + kRowsQ * kD * 2 + 1024;

__device__ __forceinline__ uint32_t smem_u32(const void* p) { return (uint32_t)__cvta_generic_to_shared(p); }
__device__ __forceinline__ void mbar_init(uint32_t bar, uint32_t cnt) {
    asm volatile("mbarrier.init.shared::cta.b64 [%0], %1;" ::"r"(bar), "r"(cnt) : "memory");
}
__device__ __forceinline__ void mbar_expect_tx(uint32_t bar, uint32_t bytes) {
    asm volatile("mbarrier.arrive.expect_tx.shared::cta.b64 _, [%0], %1;" ::"r"(bar), "r"(bytes) : "memory");
}
__device__ __forceinline__ void mbar_arrive(uint32_t bar) {
    asm volatile("mbarrier.arrive.shared::cta.b64 _, [%0];" ::"r"(bar) : "memory");
}
__device__ __forceinline__ void mbar_wait(uint32_t bar, uint32_t parity) {
    asm volatile(
        "{\n"
        ".reg .pred p;\n"
        "WAIT_LOOP:\n"
        "mbarrier.try_wait.parity.shared::cta.b64 p, [%0], %1;\n"
        "@p bra WAIT_DONE;\n"
        "bra WAIT_LOOP;\n"
        "WAIT_DONE:\n"
        "}\n" ::"r"(bar), "r"(parity) : "memory");
}
__device__ __forceinline__ bool mbar_test(uint32_t bar, uint32_t parity) {
    uint32_t ok;
    asm volatile("{\n.reg .pred p;\nmbarrier.test_wait.parity.shared::cta.b64 p, [%1], %2;\nselp.u32 %0, 1, 0, p;\n}\n"
                 : "=r"(ok) : "r"(bar), "r"(parity) : "memory");
    return ok != 0;
}
__device__ __forceinline__ void tma_load(uint32_t dst, const CUtensorMap* tm, uint32_t bar, int unit) {
    uint64_t policy;
    asm("createpolicy.fractional.L2::evict_first.b64 %0, 1.0;" : "=l"(policy));
    asm volatile(
        "cp.async.bulk.tensor.2d.shared::cluster.global.mbarrier::complete_tx::bytes.L2::cache_hint"
        " [%0], [%1, {%3, %4}], [%2], %5;"
        ::"r"(dst), "l"(tm), "r"(bar), "r"(0), "r"(unit), "l"(policy) : "memory");
}
__device__ __forceinline__ void wg_fence() { asm volatile("wgmma.fence.sync.aligned;" ::: "memory"); }
__device__ __forceinline__ void wg_commit() { asm volatile("wgmma.commit_group.sync.aligned;" ::: "memory"); }
__device__ __forceinline__ void wg_wait() { asm volatile("wgmma.wait_group.sync.aligned 0;" ::: "memory"); }

__device__ __forceinline__ uint64_t make_desc(uint32_t addr) {
    return (uint64_t)((addr & 0x3FFFF) >> 4) | ((uint64_t)1 << 16) | ((uint64_t)(1024 >> 4) << 32) | ((uint64_t)1 << 62);
}

__device__ __forceinline__ void wgmma_qk(float (&d)[64], const uint32_t (&a)[4], uint64_t desc, int scale_d) {
    asm volatile(
        "{\n.reg .pred p;\nsetp.ne.b32 p, %69, 0;\n"
        "wgmma.mma_async.sync.aligned.m64n128k16.f32.bf16.bf16 "
        "{%0,%1,%2,%3,%4,%5,%6,%7,%8,%9,%10,%11,%12,%13,%14,%15,"
        "%16,%17,%18,%19,%20,%21,%22,%23,%24,%25,%26,%27,%28,%29,%30,%31,"
        "%32,%33,%34,%35,%36,%37,%38,%39,%40,%41,%42,%43,%44,%45,%46,%47,"
        "%48,%49,%50,%51,%52,%53,%54,%55,%56,%57,%58,%59,%60,%61,%62,%63},"
        "{%64,%65,%66,%67}, %68, p, 1, 1, 0;\n}\n"
        : "+f"(d[0]), "+f"(d[1]), "+f"(d[2]), "+f"(d[3]), "+f"(d[4]), "+f"(d[5]), "+f"(d[6]), "+f"(d[7]),
          "+f"(d[8]), "+f"(d[9]), "+f"(d[10]), "+f"(d[11]), "+f"(d[12]), "+f"(d[13]), "+f"(d[14]), "+f"(d[15]),
          "+f"(d[16]), "+f"(d[17]), "+f"(d[18]), "+f"(d[19]), "+f"(d[20]), "+f"(d[21]), "+f"(d[22]), "+f"(d[23]),
          "+f"(d[24]), "+f"(d[25]), "+f"(d[26]), "+f"(d[27]), "+f"(d[28]), "+f"(d[29]), "+f"(d[30]), "+f"(d[31]),
          "+f"(d[32]), "+f"(d[33]), "+f"(d[34]), "+f"(d[35]), "+f"(d[36]), "+f"(d[37]), "+f"(d[38]), "+f"(d[39]),
          "+f"(d[40]), "+f"(d[41]), "+f"(d[42]), "+f"(d[43]), "+f"(d[44]), "+f"(d[45]), "+f"(d[46]), "+f"(d[47]),
          "+f"(d[48]), "+f"(d[49]), "+f"(d[50]), "+f"(d[51]), "+f"(d[52]), "+f"(d[53]), "+f"(d[54]), "+f"(d[55]),
          "+f"(d[56]), "+f"(d[57]), "+f"(d[58]), "+f"(d[59]), "+f"(d[60]), "+f"(d[61]), "+f"(d[62]), "+f"(d[63])
        : "r"(a[0]), "r"(a[1]), "r"(a[2]), "r"(a[3]), "l"(desc), "r"(scale_d));
}

__device__ __forceinline__ void wgmma_pv(float (&d)[32], const uint32_t (&a)[4], uint64_t desc) {
    asm volatile(
        "wgmma.mma_async.sync.aligned.m64n64k16.f32.bf16.bf16 "
        "{%0,%1,%2,%3,%4,%5,%6,%7,%8,%9,%10,%11,%12,%13,%14,%15,"
        "%16,%17,%18,%19,%20,%21,%22,%23,%24,%25,%26,%27,%28,%29,%30,%31},"
        "{%32,%33,%34,%35}, %36, 1, 1, 1, 1;\n"
        : "+f"(d[0]), "+f"(d[1]), "+f"(d[2]), "+f"(d[3]), "+f"(d[4]), "+f"(d[5]), "+f"(d[6]), "+f"(d[7]),
          "+f"(d[8]), "+f"(d[9]), "+f"(d[10]), "+f"(d[11]), "+f"(d[12]), "+f"(d[13]), "+f"(d[14]), "+f"(d[15]),
          "+f"(d[16]), "+f"(d[17]), "+f"(d[18]), "+f"(d[19]), "+f"(d[20]), "+f"(d[21]), "+f"(d[22]), "+f"(d[23]),
          "+f"(d[24]), "+f"(d[25]), "+f"(d[26]), "+f"(d[27]), "+f"(d[28]), "+f"(d[29]), "+f"(d[30]), "+f"(d[31])
        : "r"(a[0]), "r"(a[1]), "r"(a[2]), "r"(a[3]), "l"(desc));
}

__device__ __forceinline__ uint32_t ldg_u32(const uint32_t* p) {
    uint32_t v; asm volatile("ld.global.u32 %0, [%1];" : "=r"(v) : "l"(p) : "memory"); return v;
}
__device__ __forceinline__ float ex2(float x) { float y; asm("ex2.approx.ftz.f32 %0, %1;" : "=f"(y) : "f"(x)); return y; }
__device__ __forceinline__ uint32_t pack_bf16(float lo, float hi) {
    uint32_t r; asm("cvt.rn.bf16x2.f32 %0, %1, %2;" : "=r"(r) : "f"(hi), "f"(lo)); return r;
}

__device__ unsigned int g_landed;

__device__ __forceinline__ void chunk_of(int j, bool& is_v, int& tile) {
    is_v = (j / kRun) & 1;
    tile = (j / (2 * kRun)) * kRun + j % kRun;
}

__global__ void __launch_bounds__(kThreads, 1)
gqa_decode_kernel(const __grid_constant__ CUtensorMap tmK, const __grid_constant__ CUtensorMap tmV,
                  const __nv_bfloat16* __restrict__ q, __nv_bfloat16* __restrict__ out) {
    extern __shared__ uint8_t smem_raw[];
    __shared__ __align__(8) uint64_t bars[2 * kStages];
    __shared__ volatile int s_pace[3];
    const int bh = blockIdx.x;
    const int unit0 = bh * (kSk * 2);
    const int lane = threadIdx.x & 31;

    if (threadIdx.x == 128) {
        const uint32_t tiles = (smem_u32(smem_raw) + 1023u) & ~1023u;
        const uint32_t full0 = smem_u32(&bars[0]), empty0 = full0 + 8 * kStages;
#pragma unroll
        for (int j = 0; j < kWindow; j++) mbar_init(full0 + 8 * j, 1);
        asm volatile("fence.mbarrier_init.release.cluster;" ::: "memory");
#pragma unroll
        for (int j = 0; j < kWindow; j++) {
            bool is_v; int tile;
            chunk_of(j, is_v, tile);
            mbar_expect_tx(full0 + 8 * j, kTileBytes);
            tma_load(tiles + j * kTileBytes, is_v ? &tmV : &tmK, full0 + 8 * j, unit0 + tile * kTileUnits);
        }
#pragma unroll
        for (int s = kWindow; s < kStages; s++) mbar_init(full0 + 8 * s, 1);
#pragma unroll
        for (int s = 0; s < kStages; s++) mbar_init(empty0 + 8 * s, 4);
        asm volatile("fence.mbarrier_init.release.cluster;" ::: "memory");
        s_pace[0] = 0; s_pace[1] = 0;
    }

    if (threadIdx.x >= 160) {
        asm volatile("bar.sync 2, 64;" ::: "memory");
        if (lane == 0) {
            int best = 0;
            while (!s_pace[1]) {
                unsigned v;
                asm volatile("ld.relaxed.gpu.global.u32 %0, [%1];" : "=r"(v) : "l"(&g_landed) : "memory");
                best = max(best, (int)v);
                s_pace[0] = best;
            }
        }
    } else if (threadIdx.x >= 128) {
        const uint32_t tiles = (smem_u32(smem_raw) + 1023u) & ~1023u;
        const uint32_t full0 = smem_u32(&bars[0]), empty0 = full0 + 8 * kStages;
        __syncwarp();
        asm volatile("bar.arrive 1, 160;" ::: "memory");
        asm volatile("bar.arrive 2, 64;" ::: "memory");
        bool inflight = lane < kWindow;
        uint32_t fph = 0;
        int issued = kWindow, arrived = 0, slot = kWindow % kStages, eph = (kWindow / kStages) & 1;
        while (issued < kChunks) {
            const bool rdy = inflight && mbar_test(full0 + 8 * lane, fph);
            const int nrdy = __popc(__ballot_sync(0xffffffffu, rdy));
            arrived += nrdy;
            if (nrdy && lane == 0) asm volatile("red.relaxed.gpu.global.add.u32 [%0], %1;" ::"l"(&g_landed), "r"(nrdy) : "memory");
            const int credit = __shfl_sync(0xffffffffu, s_pace[0], 0) + kCredit - bh;
            if (rdy) { inflight = false; fph ^= 1; }
            const uint32_t busy = __ballot_sync(0xffffffffu, inflight);
            while (issued < kChunks &&
                   (issued - arrived < kMinFlight ||
                    (issued - arrived < kMaxFlight &&
                     issued * kNumCta + max(0, issued - kTaperFrom) * kTaperStep <= credit))) {
                if (((busy >> slot) & 1) || !__all_sync(0xffffffffu, mbar_test(empty0 + 8 * slot, eph ^ 1))) break;
                if (lane == slot) {
                    bool is_v; int tile;
                    chunk_of(issued, is_v, tile);
                    mbar_expect_tx(full0 + 8 * slot, kTileBytes);
                    tma_load(tiles + slot * kTileBytes, is_v ? &tmV : &tmK, full0 + 8 * slot, unit0 + tile * kTileUnits);
                    inflight = true;
                }
                issued++;
                if (++slot == kStages) { slot = 0; eph ^= 1; }
            }
        }
        if (lane == 0) {
            s_pace[1] = 1;
            const unsigned rest = kChunks - arrived;
            if (atomicAdd(&g_landed, rest) + rest == kNumCta * kChunks) atomicExch(&g_landed, 0u);
        }
    } else {
        const int warp = __shfl_sync(0xffffffffu, threadIdx.x >> 5, 0);
        const uint32_t tiles = __shfl_sync(0xffffffffu, (smem_u32(smem_raw) + 1023u) & ~1023u, 0);
        const uint32_t full0 = __shfl_sync(0xffffffffu, smem_u32(&bars[0]), 0), empty0 = full0 + 8 * kStages;
        const int g = lane >> 2, t = lane & 3;
        {
            uint32_t t0, t1;
            asm volatile("mov.u32 %0, %clock;" : "=r"(t0) :: "memory");
            do { asm volatile("mov.u32 %0, %clock;" : "=r"(t1) :: "memory"); } while (t1 - t0 < kQDelay);
        }
        uint32_t qa[4][4];
        {
            const uint32_t* qp = reinterpret_cast<const uint32_t*>(q + (size_t)(bh * kRowsQ + warp * 8 + g) * kD) + t;
#pragma unroll
            for (int kk = 0; kk < 4; kk++) {
                qa[kk][0] = ldg_u32(qp + kk * 8);
                qa[kk][1] = ldg_u32(qp + 32 + kk * 8);
                qa[kk][2] = ldg_u32(qp + kk * 8 + 4);
                qa[kk][3] = ldg_u32(qp + 32 + kk * 8 + 4);
            }
        }
        uint4* op = reinterpret_cast<uint4*>(out + (size_t)(bh * kRowsQ + warp * 8 + (lane >> 4)) * kD) + (lane & 15);
        asm volatile("add.u64 %0, %0, 0;" : "+l"(op));
        float o[32];
#pragma unroll
        for (int i = 0; i < 32; i++) o[i] = 0.f;
        float m = -INFINITY;
        float mo = -INFINITY;
        float l = 0.f;
        float sq[kRun][16];
        const float c = 0.08838834764831845f * 1.4426950408889634f;
        asm volatile("bar.sync 1, 160;" ::: "memory");

        auto qk_step = [&](float (&dst)[16], int s, int ph) {
            float sc[64];
            mbar_wait(full0 + 8 * s, ph);
            const uint64_t dk = make_desc(tiles + s * kTileBytes);
            wg_fence();
#pragma unroll
            for (int kk = 0; kk < 4; kk++) wgmma_qk(sc, qa[kk], dk + kk * 2, kk);
            wg_commit();
            wg_wait();
            if (lane == 0) mbar_arrive(empty0 + 8 * s);
#pragma unroll
            for (int i = 0; i < 64; i++) asm volatile("" : "+f"(sc[i]) :: "memory");
#pragma unroll
            for (int i = 0; i < 16; i++) dst[i] = sc[4 * i] + sc[4 * i + 3];
            float mx[4];
#pragma unroll
            for (int i = 0; i < 4; i++) mx[i] = fmaxf(fmaxf(dst[4 * i], dst[4 * i + 1]), fmaxf(dst[4 * i + 2], dst[4 * i + 3]));
            float mm = fmaxf(fmaxf(mx[0], mx[1]), fmaxf(mx[2], mx[3]));
            mm = fmaxf(mm, __shfl_xor_sync(0xffffffffu, mm, 1));
            mm = fmaxf(mm, __shfl_xor_sync(0xffffffffu, mm, 2));
            m = fmaxf(m, mm);
        };
        auto expo = [&](float (&x)[16]) {
            const float mc = m * c;
            float ps[4] = {0.f, 0.f, 0.f, 0.f};
#pragma unroll
            for (int j = 0; j < 16; j++) { x[j] = ex2(fmaf(x[j], c, -mc)); ps[j & 3] += x[j]; }
            return (ps[0] + ps[1]) + (ps[2] + ps[3]);
        };
        auto make_frag = [&](const float (&x)[16], float f, uint32_t (&pa)[8][4]) {
#pragma unroll
            for (int j = 0; j < 8; j++) {
                const uint32_t pk = pack_bf16(x[2 * j] * f, x[2 * j + 1] * f);
                pa[j][0] = pk & 0xFFFFu;
                pa[j][1] = pk << 16;
                pa[j][2] = pk >> 16;
                pa[j][3] = pk & 0xFFFF0000u;
#pragma unroll
                for (int r = 0; r < 4; r++) asm volatile("" : "+r"(pa[j][r]));
            }
        };
        auto scale_o = [&](float f) {
#pragma unroll
            for (int i = 0; i < 32; i++) { o[i] *= f; asm volatile("" : "+f"(o[i])); }
        };
        auto pv_issue = [&](const uint32_t (&pa)[8][4], int slot, int phase) {
            mbar_wait(full0 + 8 * slot, phase);
            const uint64_t dv = make_desc(tiles + slot * kTileBytes);
            wg_fence();
#pragma unroll
            for (int j = 0; j < 8; j++) wgmma_pv(o, pa[j], dv + j * (2048 >> 4));
            wg_commit();
        };

#pragma unroll 1
        for (int run = 0; run < kNumTiles / kRun - 1; run++) {
#pragma unroll
            for (int i = 0; i < kRun; i++) qk_step(sq[i], i, run & 1);
            const float alpha = ex2((mo - m) * c);
            mo = m;
            l *= alpha;
            scale_o(alpha);
#pragma unroll
            for (int i = 0; i < kRun; i++) {
                uint32_t pa[8][4];
                l += expo(sq[i]);
                make_frag(sq[i], 1.f, pa);
                pv_issue(pa, kRun + i, run & 1);
                wg_wait();
                if (lane == 0) mbar_arrive(empty0 + 8 * (kRun + i));
            }
        }
#pragma unroll
        for (int i = 0; i < kRun; i++) qk_step(sq[i], i, (kNumTiles / kRun - 1) & 1);
        const float alpha = ex2((mo - m) * c);
        l *= alpha;
#pragma unroll
        for (int i = 0; i < kRun; i++) l += expo(sq[i]);
        l += __shfl_xor_sync(0xffffffffu, l, 1);
        l += __shfl_xor_sync(0xffffffffu, l, 2);
        float inv;
        asm("rcp.approx.ftz.f32 %0, %1;" : "=f"(inv) : "f"(l));
        scale_o(alpha * inv);
        uint32_t pa[kRun][8][4];
#pragma unroll
        for (int i = 0; i < kRun; i++) make_frag(sq[i], inv, pa[i]);
        uint32_t st_addr[4], ld_addr[4];
#pragma unroll
        for (int h = 0; h < 4; h++) {
            const uint32_t stage = tiles + kStages * kTileBytes + warp * 2048;
            st_addr[h] = stage + (lane & 7) * 256 + (((4 * h + (lane >> 3)) ^ (lane & 7)) << 4);
            ld_addr[h] = stage + (lane >> 4) * 256 + h * 512 + (((lane & 15) ^ (2 * h + (lane >> 4))) << 4);
        }
        {
            uint32_t x = st_addr[0] | st_addr[1] | st_addr[2] | st_addr[3] | ld_addr[0] | ld_addr[1] | ld_addr[2] | ld_addr[3];
#pragma unroll
            for (int i = 0; i < 32; i++) x |= __float_as_uint(o[i]);
#pragma unroll
            for (int i = 0; i < kRun; i++)
#pragma unroll
                for (int j = 0; j < 8; j++) x |= pa[i][j][0] | pa[i][j][1] | pa[i][j][2] | pa[i][j][3];
            s_pace[2] = x;
        }
#pragma unroll
        for (int i = 0; i < kRun; i++) {
            const int j = kChunks - kRun + i;
            pv_issue(pa[i], j % kStages, (j / kStages) & 1);
        }
        wg_wait();
#pragma unroll
        for (int i = 0; i < 32; i++) asm volatile("" : "+f"(o[i]) :: "memory");
#pragma unroll
        for (int h = 0; h < 4; h++) {
            const int e = (h >> 1) * 2, i0 = (h & 1) * 4;
            asm volatile("stmatrix.sync.aligned.m8n8.x4.shared.b16 [%0], {%1,%2,%3,%4};"
                         ::"r"(st_addr[h]),
                           "r"(pack_bf16(o[4 * i0 + e], o[4 * i0 + e + 1])), "r"(pack_bf16(o[4 * i0 + 4 + e], o[4 * i0 + 5 + e])),
                           "r"(pack_bf16(o[4 * i0 + 8 + e], o[4 * i0 + 9 + e])), "r"(pack_bf16(o[4 * i0 + 12 + e], o[4 * i0 + 13 + e])) : "memory");
        }
        __syncwarp();
#pragma unroll
        for (int h = 0; h < 4; h++) {
            uint32_t a0, a1, a2, a3;
            asm volatile("ld.shared.v4.b32 {%0,%1,%2,%3}, [%4];" : "=r"(a0), "=r"(a1), "=r"(a2), "=r"(a3)
                         : "r"(ld_addr[h]) : "memory");
            asm volatile("st.global.v4.u32 [%0], {%1,%2,%3,%4};" ::"l"(op + h * 2 * (kD / 8)), "r"(a0), "r"(a1), "r"(a2), "r"(a3) : "memory");
        }
    }
}

typedef CUresult (*EncodeTiledFn)(CUtensorMap*, CUtensorMapDataType, cuuint32_t, void*, const cuuint64_t*,
                                  const cuuint64_t*, const cuuint32_t*, const cuuint32_t*, CUtensorMapInterleave,
                                  CUtensorMapSwizzle, CUtensorMapL2promotion, CUtensorMapFloatOOBfill);

void make_map(EncodeTiledFn enc, CUtensorMap* tm, const void* base) {
    const cuuint64_t dims[2] = {64, (cuuint64_t)kB * kHkv * kSk * 2};
    const cuuint64_t strides[1] = {128};
    const cuuint32_t box[2] = {64, (cuuint32_t)kTileUnits};
    const cuuint32_t estr[2] = {1, 1};
    enc(tm, CU_TENSOR_MAP_DATA_TYPE_BFLOAT16, 2, const_cast<void*>(base), dims, strides, box, estr,
        CU_TENSOR_MAP_INTERLEAVE_NONE, CU_TENSOR_MAP_SWIZZLE_128B, CU_TENSOR_MAP_L2_PROMOTION_NONE,
        CU_TENSOR_MAP_FLOAT_OOB_FILL_NONE);
}

}

extern "C" void kernel_launch(void* const* d_in, const int* in_sizes, int n_in, void* d_out, int out_size) {
    (void)in_sizes; (void)n_in; (void)out_size;
    cudaLaunchAttribute attr;
    attr.id = cudaLaunchAttributeClusterDimension;
    attr.val.clusterDim.x = 2; attr.val.clusterDim.y = 1; attr.val.clusterDim.z = 1;
    cudaLaunchConfig_t cfg = {};
    cfg.gridDim = dim3(kNumCta); cfg.blockDim = dim3(kThreads); cfg.dynamicSmemBytes = kSmemBytes;
    cfg.stream = cudaStreamPerThread; cfg.attrs = &attr; cfg.numAttrs = 1;

    static EncodeTiledFn enc = nullptr;
    static unsigned cluster = 1;
    if (!enc) {
        cudaDriverEntryPointQueryResult qr;
        cudaGetDriverEntryPoint("cuTensorMapEncodeTiled", (void**)&enc, cudaEnableDefault, &qr);
        cudaFuncSetAttribute(gqa_decode_kernel, cudaFuncAttributeMaxDynamicSharedMemorySize, kSmemBytes);
        int n = 0;
        if (cudaOccupancyMaxActiveClusters(&n, gqa_decode_kernel, &cfg) == cudaSuccess && 2 * n >= kNumCta) cluster = 2;
        (void)cudaGetLastError();
    }
    attr.val.clusterDim.x = cluster;
    CUtensorMap tmK, tmV;
    make_map(enc, &tmK, d_in[1]);
    make_map(enc, &tmV, d_in[2]);
    cudaLaunchKernelEx(&cfg, gqa_decode_kernel, tmK, tmV, (const __nv_bfloat16*)d_in[0], (__nv_bfloat16*)d_out);
}
```
